```python
import torch

def _softmax(x, axis=-1):
    return torch.softmax(x, dim=axis)
def _gelu(x):
    return torch.nn.functional.gelu(x, approximate="tanh")
def _silu(x):
    return torch.nn.functional.silu(x)
def _sigmoid(x):
    return torch.sigmoid(x)
def _layernorm(x, axis=-1, eps=1e-5):
    m = x.mean(dim=axis, keepdim=True)
    v = x.var(dim=axis, keepdim=True, unbiased=False)
    return (x - m) / torch.sqrt(v + eps)
def _scatter_add(tgt, idx, src, axis=0):
    return tgt.clone().index_add_(axis, idx, src)
def _segment_sum(src, seg, n):
    out = torch.zeros((n,) + src.shape[1:], dtype=src.dtype)
    return out.index_add_(0, seg, src)
def _pad(x, pw):
    flat = tuple(v for pair in reversed(pw) for v in pair)
    return torch.nn.functional.pad(x, flat)

kernel_name = 'gated_mix__compressed_kv_cla__geglu_ffn__prompt'

def setup_inputs():

    _w = (lambda a: (lambda t: t.to(torch.bfloat16) if t.is_floating_point() else t)(torch.as_tensor(a)))
    def _A_setup():
        B, H, Sq, Sk, D, M = 1, 32, 2048, 2048, 128, 512
        Dc = 4 * D
        return {
            "x": _w((lambda *s: torch.randn(*s, dtype=torch.bfloat16) * 0.05)(B, Sq, M)),
            "c_kv": _w((lambda *s: torch.randn(*s, dtype=torch.bfloat16) * 0.8)(B, Sk, Dc)),
            "w_q": _w((lambda *s: torch.randn(*s, dtype=torch.bfloat16) * 6.4)(M, H, D) * (M ** -0.5)),
            "w_uk": _w((lambda *s: torch.randn(*s, dtype=torch.bfloat16) * 6.4)(Dc, H, D) * (Dc ** -0.5)),
            "w_uv": _w((lambda *s: torch.randn(*s, dtype=torch.bfloat16) * 0.8)(Dc, H, D) * (Dc ** -0.5)),
            "w_o": _w((lambda *s: torch.randn(*s, dtype=torch.bfloat16) * 0.8)(H, D, M) * ((H * D) ** -0.5)),
        }
    _A_in = _A_setup()

    def _B_setup():
        B, S, D, F = 1, 2048, 512, 1792
        return {
            "x": _w((lambda *s: torch.randn(*s, dtype=torch.bfloat16) * 0.05)(B, S, D)),
            "w_gate": _w((lambda *s: torch.randn(*s, dtype=torch.bfloat16) * 0.2)(D, F)),
            "w_up": _w((lambda *s: torch.randn(*s, dtype=torch.bfloat16) * 0.2)(D, F)),
            "w_down": _w((lambda *s: torch.randn(*s, dtype=torch.bfloat16) * 0.2)(F, D)),
        }
    _B_in = _B_setup()

    return {
        "A_x": _A_in["x"],
        "A_c_kv": _A_in["c_kv"],
        "A_w_q": _A_in["w_q"],
        "A_w_uk": _A_in["w_uk"],
        "A_w_uv": _A_in["w_uv"],
        "A_w_o": _A_in["w_o"],
        "B_x": _B_in["x"],
        "B_w_gate": _B_in["w_gate"],
        "B_w_up": _B_in["w_up"],
        "B_w_down": _B_in["w_down"],
        "gate_w": _w((lambda *s: torch.randn(*s, dtype=torch.bfloat16) * 0.05)(512) * 16.0),
    }

def reference(A_x, A_c_kv, A_w_q, A_w_uk, A_w_uv, A_w_o, B_x, B_w_gate, B_w_up, B_w_down, gate_w):
    def _A_ref(x, c_kv, w_q, w_uk, w_uv, w_o):
        B, Sq, M = x.shape[0], x.shape[1], x.shape[2]
        Sk = c_kv.shape[1]
        H, D = w_q.shape[1], w_q.shape[2]
        q = torch.einsum("bqm,mhd->bhqd", x, w_q)
        k = torch.einsum("bkc,chd->bhkd", c_kv, w_uk)
        v = torch.einsum("bkc,chd->bhkd", c_kv, w_uv)
        scores = torch.einsum("bhqd,bhkd->bhqk", q, k) * (D ** -0.5)
        off = Sk - Sq
        qi = torch.arange(Sq)[:, None]
        kj = torch.arange(Sk)[None, :]
        cmask = kj <= (qi + off)
        scores = torch.where(cmask[None, None], scores, -1e9)
        p = _softmax(scores, axis=-1)
        ctx = torch.einsum("bhqk,bhkd->bhqd", p, v)
        return torch.einsum("bhqd,hdm->bqm", ctx, w_o)

    def _B_ref(x, w_gate, w_up, w_down):
        return (_gelu(x @ w_gate) * (x @ w_up)) @ w_down

    x = A_x
    g = _sigmoid((x * gate_w).sum(-1, keepdims=True))
    a = _A_ref(x, A_c_kv, A_w_q, A_w_uk, A_w_uv, A_w_o)
    b = _B_ref(x, B_w_gate, B_w_up, B_w_down)
    return g * a + (1 - g) * b
```

```cpp
#include <cuda_runtime.h>
#include <cuda_bf16.h>
#include <cuda.h>
#include <stdint.h>

__device__ __forceinline__ void wgmma_ss_n256_tb(float (&d)[128], uint64_t da, uint64_t db, int scaleD) {
  asm volatile("{\n.reg .pred p;\nsetp.ne.b32 p, %130, 0;\n"
    "wgmma.mma_async.sync.aligned.m64n256k16.f32.bf16.bf16 {%0, %1, %2, %3, %4, %5, %6, %7, %8, %9, %10, %11, %12, %13, %14, %15, %16, %17, %18, %19, %20, %21, %22, %23, %24, %25, %26, %27, %28, %29, %30, %31, %32, %33, %34, %35, %36, %37, %38, %39, %40, %41, %42, %43, %44, %45, %46, %47, %48, %49, %50, %51, %52, %53, %54, %55, %56, %57, %58, %59, %60, %61, %62, %63, %64, %65, %66, %67, %68, %69, %70, %71, %72, %73, %74, %75, %76, %77, %78, %79, %80, %81, %82, %83, %84, %85, %86, %87, %88, %89, %90, %91, %92, %93, %94, %95, %96, %97, %98, %99, %100, %101, %102, %103, %104, %105, %106, %107, %108, %109, %110, %111, %112, %113, %114, %115, %116, %117, %118, %119, %120, %121, %122, %123, %124, %125, %126, %127}, %128, %129, p, 1, 1, 0, 1;\n}\n"
    : "+f"(d[0]), "+f"(d[1]), "+f"(d[2]), "+f"(d[3]), "+f"(d[4]), "+f"(d[5]), "+f"(d[6]), "+f"(d[7]), "+f"(d[8]), "+f"(d[9]), "+f"(d[10]), "+f"(d[11]), "+f"(d[12]), "+f"(d[13]), "+f"(d[14]), "+f"(d[15]), "+f"(d[16]), "+f"(d[17]), "+f"(d[18]), "+f"(d[19]), "+f"(d[20]), "+f"(d[21]), "+f"(d[22]), "+f"(d[23]), "+f"(d[24]), "+f"(d[25]), "+f"(d[26]), "+f"(d[27]), "+f"(d[28]), "+f"(d[29]), "+f"(d[30]), "+f"(d[31]), "+f"(d[32]), "+f"(d[33]), "+f"(d[34]), "+f"(d[35]), "+f"(d[36]), "+f"(d[37]), "+f"(d[38]), "+f"(d[39]), "+f"(d[40]), "+f"(d[41]), "+f"(d[42]), "+f"(d[43]), "+f"(d[44]), "+f"(d[45]), "+f"(d[46]), "+f"(d[47]), "+f"(d[48]), "+f"(d[49]), "+f"(d[50]), "+f"(d[51]), "+f"(d[52]), "+f"(d[53]), "+f"(d[54]), "+f"(d[55]), "+f"(d[56]), "+f"(d[57]), "+f"(d[58]), "+f"(d[59]), "+f"(d[60]), "+f"(d[61]), "+f"(d[62]), "+f"(d[63]), "+f"(d[64]), "+f"(d[65]), "+f"(d[66]), "+f"(d[67]), "+f"(d[68]), "+f"(d[69]), "+f"(d[70]), "+f"(d[71]), "+f"(d[72]), "+f"(d[73]), "+f"(d[74]), "+f"(d[75]), "+f"(d[76]), "+f"(d[77]), "+f"(d[78]), "+f"(d[79]), "+f"(d[80]), "+f"(d[81]), "+f"(d[82]), "+f"(d[83]), "+f"(d[84]), "+f"(d[85]), "+f"(d[86]), "+f"(d[87]), "+f"(d[88]), "+f"(d[89]), "+f"(d[90]), "+f"(d[91]), "+f"(d[92]), "+f"(d[93]), "+f"(d[94]), "+f"(d[95]), "+f"(d[96]), "+f"(d[97]), "+f"(d[98]), "+f"(d[99]), "+f"(d[100]), "+f"(d[101]), "+f"(d[102]), "+f"(d[103]), "+f"(d[104]), "+f"(d[105]), "+f"(d[106]), "+f"(d[107]), "+f"(d[108]), "+f"(d[109]), "+f"(d[110]), "+f"(d[111]), "+f"(d[112]), "+f"(d[113]), "+f"(d[114]), "+f"(d[115]), "+f"(d[116]), "+f"(d[117]), "+f"(d[118]), "+f"(d[119]), "+f"(d[120]), "+f"(d[121]), "+f"(d[122]), "+f"(d[123]), "+f"(d[124]), "+f"(d[125]), "+f"(d[126]), "+f"(d[127]) : "l"(da), "l"(db), "r"(scaleD));
}
__device__ __forceinline__ void wgmma_ss_n64_tb(float (&d)[32], uint64_t da, uint64_t db, int scaleD) {
  asm volatile("{\n.reg .pred p;\nsetp.ne.b32 p, %34, 0;\n"
    "wgmma.mma_async.sync.aligned.m64n64k16.f32.bf16.bf16 {%0, %1, %2, %3, %4, %5, %6, %7, %8, %9, %10, %11, %12, %13, %14, %15, %16, %17, %18, %19, %20, %21, %22, %23, %24, %25, %26, %27, %28, %29, %30, %31}, %32, %33, p, 1, 1, 0, 1;\n}\n"
    : "+f"(d[0]), "+f"(d[1]), "+f"(d[2]), "+f"(d[3]), "+f"(d[4]), "+f"(d[5]), "+f"(d[6]), "+f"(d[7]), "+f"(d[8]), "+f"(d[9]), "+f"(d[10]), "+f"(d[11]), "+f"(d[12]), "+f"(d[13]), "+f"(d[14]), "+f"(d[15]), "+f"(d[16]), "+f"(d[17]), "+f"(d[18]), "+f"(d[19]), "+f"(d[20]), "+f"(d[21]), "+f"(d[22]), "+f"(d[23]), "+f"(d[24]), "+f"(d[25]), "+f"(d[26]), "+f"(d[27]), "+f"(d[28]), "+f"(d[29]), "+f"(d[30]), "+f"(d[31]) : "l"(da), "l"(db), "r"(scaleD));
}
__device__ __forceinline__ void wgmma_rs_n128(float (&d)[64], uint32_t a0, uint32_t a1, uint32_t a2, uint32_t a3, uint64_t db, int scaleD) {
  asm volatile("{\n.reg .pred p;\nsetp.ne.b32 p, %69, 0;\n"
    "wgmma.mma_async.sync.aligned.m64n128k16.f32.bf16.bf16 {%0, %1, %2, %3, %4, %5, %6, %7, %8, %9, %10, %11, %12, %13, %14, %15, %16, %17, %18, %19, %20, %21, %22, %23, %24, %25, %26, %27, %28, %29, %30, %31, %32, %33, %34, %35, %36, %37, %38, %39, %40, %41, %42, %43, %44, %45, %46, %47, %48, %49, %50, %51, %52, %53, %54, %55, %56, %57, %58, %59, %60, %61, %62, %63}, {%64, %65, %66, %67}, %68, p, 1, 1, 0;\n}\n"
    : "+f"(d[0]), "+f"(d[1]), "+f"(d[2]), "+f"(d[3]), "+f"(d[4]), "+f"(d[5]), "+f"(d[6]), "+f"(d[7]), "+f"(d[8]), "+f"(d[9]), "+f"(d[10]), "+f"(d[11]), "+f"(d[12]), "+f"(d[13]), "+f"(d[14]), "+f"(d[15]), "+f"(d[16]), "+f"(d[17]), "+f"(d[18]), "+f"(d[19]), "+f"(d[20]), "+f"(d[21]), "+f"(d[22]), "+f"(d[23]), "+f"(d[24]), "+f"(d[25]), "+f"(d[26]), "+f"(d[27]), "+f"(d[28]), "+f"(d[29]), "+f"(d[30]), "+f"(d[31]), "+f"(d[32]), "+f"(d[33]), "+f"(d[34]), "+f"(d[35]), "+f"(d[36]), "+f"(d[37]), "+f"(d[38]), "+f"(d[39]), "+f"(d[40]), "+f"(d[41]), "+f"(d[42]), "+f"(d[43]), "+f"(d[44]), "+f"(d[45]), "+f"(d[46]), "+f"(d[47]), "+f"(d[48]), "+f"(d[49]), "+f"(d[50]), "+f"(d[51]), "+f"(d[52]), "+f"(d[53]), "+f"(d[54]), "+f"(d[55]), "+f"(d[56]), "+f"(d[57]), "+f"(d[58]), "+f"(d[59]), "+f"(d[60]), "+f"(d[61]), "+f"(d[62]), "+f"(d[63]) : "r"(a0), "r"(a1), "r"(a2), "r"(a3), "l"(db), "r"(scaleD));
}
__device__ __forceinline__ void wgmma_rs_n128_tb(float (&d)[64], uint32_t a0, uint32_t a1, uint32_t a2, uint32_t a3, uint64_t db, int scaleD) {
  asm volatile("{\n.reg .pred p;\nsetp.ne.b32 p, %69, 0;\n"
    "wgmma.mma_async.sync.aligned.m64n128k16.f32.bf16.bf16 {%0, %1, %2, %3, %4, %5, %6, %7, %8, %9, %10, %11, %12, %13, %14, %15, %16, %17, %18, %19, %20, %21, %22, %23, %24, %25, %26, %27, %28, %29, %30, %31, %32, %33, %34, %35, %36, %37, %38, %39, %40, %41, %42, %43, %44, %45, %46, %47, %48, %49, %50, %51, %52, %53, %54, %55, %56, %57, %58, %59, %60, %61, %62, %63}, {%64, %65, %66, %67}, %68, p, 1, 1, 1;\n}\n"
    : "+f"(d[0]), "+f"(d[1]), "+f"(d[2]), "+f"(d[3]), "+f"(d[4]), "+f"(d[5]), "+f"(d[6]), "+f"(d[7]), "+f"(d[8]), "+f"(d[9]), "+f"(d[10]), "+f"(d[11]), "+f"(d[12]), "+f"(d[13]), "+f"(d[14]), "+f"(d[15]), "+f"(d[16]), "+f"(d[17]), "+f"(d[18]), "+f"(d[19]), "+f"(d[20]), "+f"(d[21]), "+f"(d[22]), "+f"(d[23]), "+f"(d[24]), "+f"(d[25]), "+f"(d[26]), "+f"(d[27]), "+f"(d[28]), "+f"(d[29]), "+f"(d[30]), "+f"(d[31]), "+f"(d[32]), "+f"(d[33]), "+f"(d[34]), "+f"(d[35]), "+f"(d[36]), "+f"(d[37]), "+f"(d[38]), "+f"(d[39]), "+f"(d[40]), "+f"(d[41]), "+f"(d[42]), "+f"(d[43]), "+f"(d[44]), "+f"(d[45]), "+f"(d[46]), "+f"(d[47]), "+f"(d[48]), "+f"(d[49]), "+f"(d[50]), "+f"(d[51]), "+f"(d[52]), "+f"(d[53]), "+f"(d[54]), "+f"(d[55]), "+f"(d[56]), "+f"(d[57]), "+f"(d[58]), "+f"(d[59]), "+f"(d[60]), "+f"(d[61]), "+f"(d[62]), "+f"(d[63]) : "r"(a0), "r"(a1), "r"(a2), "r"(a3), "l"(db), "r"(scaleD));
}


namespace {

constexpr int EXP_SPLIT = 2;
constexpr int NSLOT = 7;
constexpr uint32_t UNIT = 32768;
constexpr int NCLUSTER = 66;
constexpr int NCTA = 2 * NCLUSTER;
constexpr uint32_t SMEM_BAR = NSLOT * UNIT;
constexpr uint32_t SMEM_BYTES = SMEM_BAR + 256;

enum { T_END = 0, T_G1 = 1, T_ATT = 2, T_P3 = 3 };
enum { K_KV = 0, K_Q = 1, K_FFN = 2 };

constexpr int MAXT = 18;
__constant__ uint2 c_tasks[NCLUSTER * MAXT] = {
  {0x10010071u,0x0u}, {0x10000521u,0x0u}, {0x10010671u,0x0u}, {0x10001001u,0x0u}, {0xb72u,0x0u}, {0x1032u,0x0u}, {0x1332u,0x0u}, {0x1852u,0x0u}, {0x1c12u,0x0u}, {0x8abd0063u,0x2eaeu}, {0x0u,0x0u}, {0x0u,0x0u}, {0x0u,0x0u}, {0x0u,0x0u}, {0x0u,0x0u}, {0x0u,0x0u}, {0x0u,0x0u}, {0x0u,0x0u},
  {0x10010061u,0x0u}, {0x10000531u,0x0u}, {0x10000a41u,0x0u}, {0x72u,0x0u}, {0x622u,0x0u}, {0xd22u,0x0u}, {0x1102u,0x0u}, {0x1462u,0x0u}, {0x1d42u,0x0u}, {0x8cc90033u,0x2eaeu}, {0x0u,0x0u}, {0x0u,0x0u}, {0x0u,0x0u}, {0x0u,0x0u}, {0x0u,0x0u}, {0x0u,0x0u}, {0x0u,0x0u}, {0x0u,0x0u},
  {0x10000331u,0x0u}, {0x10000851u,0x0u}, {0x10010611u,0x0u}, {0x10010811u,0x0u}, {0x10001231u,0x0u}, {0x10001421u,0x0u}, {0x10001611u,0x0u}, {0x10001801u,0x0u}, {0x10010d01u,0x0u}, {0x10010e11u,0x0u}, {0x10010f21u,0x0u}, {0x10020041u,0x0u}, {0x10020331u,0x0u}, {0x10020621u,0x0u}, {0x10020911u,0x0u}, {0x10020c01u,0x0u}, {0x686d0043u,0x2eadu}, {0x0u,0x0u},
  {0x10010051u,0x0u}, {0x10000541u,0x0u}, {0x10000a51u,0x0u}, {0x372u,0x0u}, {0x522u,0x0u}, {0xc22u,0x0u}, {0x1002u,0x0u}, {0x1302u,0x0u}, {0x1762u,0x0u}, {0x1f32u,0x0u}, {0xad0d0163u,0x2eafu}, {0x0u,0x0u}, {0x0u,0x0u}, {0x0u,0x0u}, {0x0u,0x0u}, {0x0u,0x0u}, {0x0u,0x0u}, {0x0u,0x0u},
  {0x10010041u,0x0u}, {0x10000551u,0x0u}, {0x10000a61u,0x0u}, {0x272u,0x0u}, {0x922u,0x0u}, {0x1172u,0x0u}, {0x1942u,0x0u}, {0x1f22u,0x0u}, {0x8ecd0123u,0x2eaeu}, {0x0u,0x0u}, {0x0u,0x0u}, {0x0u,0x0u}, {0x0u,0x0u}, {0x0u,0x0u}, {0x0u,0x0u}, {0x0u,0x0u}, {0x0u,0x0u}, {0x0u,0x0u},
  {0x10000341u,0x0u}, {0x10000861u,0x0u}, {0x10010601u,0x0u}, {0x10010801u,0x0u}, {0x10001241u,0x0u}, {0x10001431u,0x0u}, {0x10001621u,0x0u}, {0x10001811u,0x0u}, {0x10001a01u,0x0u}, {0x10010e01u,0x0u}, {0x10010f11u,0x0u}, {0x10020051u,0x0u}, {0x10020341u,0x0u}, {0x10020631u,0x0u}, {0x10020921u,0x0u}, {0x10020c11u,0x0u}, {0x30010063u,0x2eacu}, {0x0u,0x0u},
  {0x10010031u,0x0u}, {0x10000561u,0x0u}, {0x10000a71u,0x0u}, {0x172u,0x0u}, {0xf72u,0x0u}, {0x1532u,0x0u}, {0x1b62u,0x0u}, {0x94d90113u,0x2eaeu}, {0x0u,0x0u}, {0x0u,0x0u}, {0x0u,0x0u}, {0x0u,0x0u}, {0x0u,0x0u}, {0x0u,0x0u}, {0x0u,0x0u}, {0x0u,0x0u}, {0x0u,0x0u}, {0x0u,0x0u},
  {0x10010021u,0x0u}, {0x10000571u,0x0u}, {0x10000b01u,0x0u}, {0x472u,0x0u}, {0xe72u,0x0u}, {0x1432u,0x0u}, {0x1a62u,0x0u}, {0x92d50023u,0x2eaeu}, {0x0u,0x0u}, {0x0u,0x0u}, {0x0u,0x0u}, {0x0u,0x0u}, {0x0u,0x0u}, {0x0u,0x0u}, {0x0u,0x0u}, {0x0u,0x0u}, {0x0u,0x0u}, {0x0u,0x0u},
  {0x10000351u,0x0u}, {0x10000871u,0x0u}, {0x10010771u,0x0u}, {0x10001061u,0x0u}, {0x10001251u,0x0u}, {0x10001441u,0x0u}, {0x10001631u,0x0u}, {0x10001821u,0x0u}, {0x10001a11u,0x0u}, {0x10001c01u,0x0u}, {0x10010f01u,0x0u}, {0x10020061u,0x0u}, {0x10020351u,0x0u}, {0x10020641u,0x0u}, {0x10020931u,0x0u}, {0x10020c21u,0x0u}, {0x2e010053u,0x2eacu}, {0x0u,0x0u},
  {0x10010011u,0x0u}, {0x10010371u,0x0u}, {0x10000b11u,0x0u}, {0x362u,0x0u}, {0x832u,0x0u}, {0x1072u,0x0u}, {0x1842u,0x0u}, {0x1802u,0x0u}, {0x1b12u,0x0u}, {0x8ecd0133u,0x2eaeu}, {0x0u,0x0u}, {0x0u,0x0u}, {0x0u,0x0u}, {0x0u,0x0u}, {0x0u,0x0u}, {0x0u,0x0u}, {0x0u,0x0u}, {0x0u,0x0u},
  {0x10010001u,0x0u}, {0x10010361u,0x0u}, {0x10010661u,0x0u}, {0x10001011u,0x0u}, {0xa72u,0x0u}, {0xf22u,0x0u}, {0x1212u,0x0u}, {0x1402u,0x0u}, {0x1602u,0x0u}, {0x1612u,0x0u}, {0x1b72u,0x0u}, {0xad0d0053u,0x2eafu}, {0x0u,0x0u}, {0x0u,0x0u}, {0x0u,0x0u}, {0x0u,0x0u}, {0x0u,0x0u}, {0x0u,0x0u},
  {0x10000361u,0x0u}, {0x10000901u,0x0u}, {0x10010761u,0x0u}, {0x10001071u,0x0u}, {0x10001261u,0x0u}, {0x10001451u,0x0u}, {0x10001641u,0x0u}, {0x10001831u,0x0u}, {0x10001a21u,0x0u}, {0x10001c11u,0x0u}, {0x10001e01u,0x0u}, {0x10020071u,0x0u}, {0x10020361u,0x0u}, {0x10020651u,0x0u}, {0x10020941u,0x0u}, {0x10020c31u,0x0u}, {0x5e610063u,0x2eadu}, {0x0u,0x0u},
  {0x10000001u,0x0u}, {0x10010351u,0x0u}, {0x10000b21u,0x0u}, {0x262u,0x0u}, {0xb32u,0x0u}, {0x1022u,0x0u}, {0x1252u,0x0u}, {0x1d02u,0x0u}, {0x1a52u,0x0u}, {0xad0d0073u,0x2eafu}, {0x0u,0x0u}, {0x0u,0x0u}, {0x0u,0x0u}, {0x0u,0x0u}, {0x0u,0x0u}, {0x0u,0x0u}, {0x0u,0x0u}, {0x0u,0x0u},
  {0x10000011u,0x0u}, {0x10010341u,0x0u}, {0x10000b31u,0x0u}, {0x462u,0x0u}, {0x822u,0x0u}, {0xf62u,0x0u}, {0x1502u,0x0u}, {0x1712u,0x0u}, {0x1a02u,0x0u}, {0x1b42u,0x0u}, {0x30010153u,0x2eacu}, {0x0u,0x0u}, {0x0u,0x0u}, {0x0u,0x0u}, {0x0u,0x0u}, {0x0u,0x0u}, {0x0u,0x0u}, {0x0u,0x0u},
  {0x10000371u,0x0u}, {0x10000911u,0x0u}, {0x10010751u,0x0u}, {0x10001101u,0x0u}, {0x10001271u,0x0u}, {0x10001461u,0x0u}, {0x10001651u,0x0u}, {0x10001841u,0x0u}, {0x10001a31u,0x0u}, {0x10001c21u,0x0u}, {0x10001e11u,0x0u}, {0x10020101u,0x0u}, {0x10020371u,0x0u}, {0x10020661u,0x0u}, {0x10020951u,0x0u}, {0x10020c41u,0x0u}, {0x8cbd0153u,0x2eaeu}, {0x0u,0x0u},
  {0x10000021u,0x0u}, {0x10010331u,0x0u}, {0x10000b41u,0x0u}, {0x62u,0x0u}, {0x722u,0x0u}, {0xe62u,0x0u}, {0x1652u,0x0u}, {0x1c32u,0x0u}, {0x86bd0073u,0x2eaeu}, {0x0u,0x0u}, {0x0u,0x0u}, {0x0u,0x0u}, {0x0u,0x0u}, {0x0u,0x0u}, {0x0u,0x0u}, {0x0u,0x0u}, {0x0u,0x0u}, {0x0u,0x0u},
  {0x10000031u,0x0u}, {0x10010321u,0x0u}, {0x10000b51u,0x0u}, {0x162u,0x0u}, {0xa22u,0x0u}, {0xd62u,0x0u}, {0x1752u,0x0u}, {0x1f52u,0x0u}, {0xad290013u,0x2eafu}, {0x0u,0x0u}, {0x0u,0x0u}, {0x0u,0x0u}, {0x0u,0x0u}, {0x0u,0x0u}, {0x0u,0x0u}, {0x0u,0x0u}, {0x0u,0x0u}, {0x0u,0x0u},
  {0x10010271u,0x0u}, {0x10000921u,0x0u}, {0x10010741u,0x0u}, {0x10001111u,0x0u}, {0x10001301u,0x0u}, {0x10001471u,0x0u}, {0x10001661u,0x0u}, {0x10001851u,0x0u}, {0x10001a41u,0x0u}, {0x10001c31u,0x0u}, {0x10001e21u,0x0u}, {0x10020111u,0x0u}, {0x10020401u,0x0u}, {0x10020671u,0x0u}, {0x10020961u,0x0u}, {0x10020c51u,0x0u}, {0x86b50163u,0x2eaeu}, {0x0u,0x0u},
  {0x10000041u,0x0u}, {0x10010311u,0x0u}, {0x10000b61u,0x0u}, {0x52u,0x0u}, {0x732u,0x0u}, {0xc62u,0x0u}, {0x1742u,0x0u}, {0x1f62u,0x0u}, {0xad2d0103u,0x2eafu}, {0x0u,0x0u}, {0x0u,0x0u}, {0x0u,0x0u}, {0x0u,0x0u}, {0x0u,0x0u}, {0x0u,0x0u}, {0x0u,0x0u}, {0x0u,0x0u}, {0x0u,0x0u},
  {0x10000051u,0x0u}, {0x10010301u,0x0u}, {0x10000b71u,0x0u}, {0x352u,0x0u}, {0xa32u,0x0u}, {0xb12u,0x0u}, {0x1142u,0x0u}, {0x1732u,0x0u}, {0x1e72u,0x0u}, {0xad290003u,0x2eafu}, {0x0u,0x0u}, {0x0u,0x0u}, {0x0u,0x0u}, {0x0u,0x0u}, {0x0u,0x0u}, {0x0u,0x0u}, {0x0u,0x0u}, {0x0u,0x0u},
  {0x10010261u,0x0u}, {0x10000931u,0x0u}, {0x10010731u,0x0u}, {0x10001121u,0x0u}, {0x10001311u,0x0u}, {0x10001501u,0x0u}, {0x10001671u,0x0u}, {0x10001861u,0x0u}, {0x10001a51u,0x0u}, {0x10001c41u,0x0u}, {0x10001e31u,0x0u}, {0x10020121u,0x0u}, {0x10020411u,0x0u}, {0x10020701u,0x0u}, {0x10020971u,0x0u}, {0x10020c61u,0x0u}, {0x8cbd0143u,0x2eaeu}, {0x0u,0x0u},
  {0x10000061u,0x0u}, {0x10000601u,0x0u}, {0x10010651u,0x0u}, {0x10001021u,0x0u}, {0x662u,0x0u}, {0xc72u,0x0u}, {0x1632u,0x0u}, {0x1f72u,0x0u}, {0xad250023u,0x2eafu}, {0x0u,0x0u}, {0x0u,0x0u}, {0x0u,0x0u}, {0x0u,0x0u}, {0x0u,0x0u}, {0x0u,0x0u}, {0x0u,0x0u}, {0x0u,0x0u}, {0x0u,0x0u},
  {0x10010251u,0x0u}, {0x10000941u,0x0u}, {0x10010721u,0x0u}, {0x10001131u,0x0u}, {0x10001321u,0x0u}, {0x10001511u,0x0u}, {0x10001701u,0x0u}, {0x10001871u,0x0u}, {0x10001a61u,0x0u}, {0x10001c51u,0x0u}, {0x10001e41u,0x0u}, {0x10020131u,0x0u}, {0x10020421u,0x0u}, {0x10020711u,0x0u}, {0x10020a01u,0x0u}, {0x10020c71u,0x0u}, {0x5a5d0173u,0x2eadu}, {0x0u,0x0u},
  {0x10000071u,0x0u}, {0x10000611u,0x0u}, {0x10000c01u,0x0u}, {0x252u,0x0u}, {0x632u,0x0u}, {0x802u,0x0u}, {0xe12u,0x0u}, {0x1012u,0x0u}, {0x1452u,0x0u}, {0x1d62u,0x0u}, {0xad1d0123u,0x2eafu}, {0x0u,0x0u}, {0x0u,0x0u}, {0x0u,0x0u}, {0x0u,0x0u}, {0x0u,0x0u}, {0x0u,0x0u}, {0x0u,0x0u},
  {0x10000101u,0x0u}, {0x10000621u,0x0u}, {0x10000c11u,0x0u}, {0x152u,0x0u}, {0x532u,0x0u}, {0x702u,0x0u}, {0xd12u,0x0u}, {0x1362u,0x0u}, {0x1c02u,0x0u}, {0x1a42u,0x0u}, {0x6a790003u,0x2eadu}, {0x0u,0x0u}, {0x0u,0x0u}, {0x0u,0x0u}, {0x0u,0x0u}, {0x0u,0x0u}, {0x0u,0x0u}, {0x0u,0x0u},
  {0x10010241u,0x0u}, {0x10000951u,0x0u}, {0x10010711u,0x0u}, {0x10001141u,0x0u}, {0x10001331u,0x0u}, {0x10001521u,0x0u}, {0x10001711u,0x0u}, {0x10001901u,0x0u}, {0x10001a71u,0x0u}, {0x10001c61u,0x0u}, {0x10001e51u,0x0u}, {0x10020141u,0x0u}, {0x10020431u,0x0u}, {0x10020721u,0x0u}, {0x10020a11u,0x0u}, {0x10020d01u,0x0u}, {0x5a5d0163u,0x2eadu}, {0x0u,0x0u},
  {0x10000111u,0x0u}, {0x10000631u,0x0u}, {0x10000c21u,0x0u}, {0x452u,0x0u}, {0x932u,0x0u}, {0xa02u,0x0u}, {0xc12u,0x0u}, {0x1262u,0x0u}, {0x1b32u,0x0u}, {0x1812u,0x0u}, {0x5e610143u,0x2eadu}, {0x0u,0x0u}, {0x0u,0x0u}, {0x0u,0x0u}, {0x0u,0x0u}, {0x0u,0x0u}, {0x0u,0x0u}, {0x0u,0x0u},
  {0x10000121u,0x0u}, {0x10000641u,0x0u}, {0x10000c31u,0x0u}, {0x342u,0x0u}, {0x942u,0x0u}, {0x602u,0x0u}, {0xf12u,0x0u}, {0x1202u,0x0u}, {0x1322u,0x0u}, {0x1902u,0x0u}, {0x1872u,0x0u}, {0x2e010163u,0x2eacu}, {0x0u,0x0u}, {0x0u,0x0u}, {0x0u,0x0u}, {0x0u,0x0u}, {0x0u,0x0u}, {0x0u,0x0u},
  {0x10010231u,0x0u}, {0x10000961u,0x0u}, {0x10010701u,0x0u}, {0x10001151u,0x0u}, {0x10001341u,0x0u}, {0x10001531u,0x0u}, {0x10001721u,0x0u}, {0x10001911u,0x0u}, {0x10001b01u,0x0u}, {0x10001c71u,0x0u}, {0x10001e61u,0x0u}, {0x10020151u,0x0u}, {0x10020441u,0x0u}, {0x10020731u,0x0u}, {0x10020a21u,0x0u}, {0x10020d11u,0x0u}, {0x84b50173u,0x2eaeu}, {0x0u,0x0u},
  {0x10000131u,0x0u}, {0x10000651u,0x0u}, {0x10000c41u,0x0u}, {0x242u,0x0u}, {0x642u,0x0u}, {0x902u,0x0u}, {0x1162u,0x0u}, {0x1962u,0x0u}, {0x36010043u,0x2eacu}, {0x0u,0x0u}, {0x0u,0x0u}, {0x0u,0x0u}, {0x0u,0x0u}, {0x0u,0x0u}, {0x0u,0x0u}, {0x0u,0x0u}, {0x0u,0x0u}, {0x0u,0x0u},
  {0x10000141u,0x0u}, {0x10000661u,0x0u}, {0x10000c51u,0x0u}, {0x442u,0x0u}, {0x542u,0x0u}, {0xf52u,0x0u}, {0x1522u,0x0u}, {0x1932u,0x0u}, {0x1c22u,0x0u}, {0x5e610073u,0x2eadu}, {0x0u,0x0u}, {0x0u,0x0u}, {0x0u,0x0u}, {0x0u,0x0u}, {0x0u,0x0u}, {0x0u,0x0u}, {0x0u,0x0u}, {0x0u,0x0u},
  {0x10010221u,0x0u}, {0x10000971u,0x0u}, {0x10000f11u,0x0u}, {0x10001161u,0x0u}, {0x10001351u,0x0u}, {0x10001541u,0x0u}, {0x10001731u,0x0u}, {0x10001921u,0x0u}, {0x10001b11u,0x0u}, {0x10001d01u,0x0u}, {0x10001e71u,0x0u}, {0x10020161u,0x0u}, {0x10020451u,0x0u}, {0x10020741u,0x0u}, {0x10020a31u,0x0u}, {0x10020d21u,0x0u}, {0x66790123u,0x2eadu}, {0x0u,0x0u},
  {0x10000151u,0x0u}, {0x10000671u,0x0u}, {0x10010641u,0x0u}, {0x10001031u,0x0u}, {0x862u,0x0u}, {0xb22u,0x0u}, {0x1132u,0x0u}, {0x1662u,0x0u}, {0x1f42u,0x0u}, {0xad150063u,0x2eafu}, {0x0u,0x0u}, {0x0u,0x0u}, {0x0u,0x0u}, {0x0u,0x0u}, {0x0u,0x0u}, {0x0u,0x0u}, {0x0u,0x0u}, {0x0u,0x0u},
  {0x10000161u,0x0u}, {0x10000701u,0x0u}, {0x10000c61u,0x0u}, {0x42u,0x0u}, {0xb42u,0x0u}, {0xe52u,0x0u}, {0x1422u,0x0u}, {0x1832u,0x0u}, {0x1e42u,0x0u}, {0xad190033u,0x2eafu}, {0x0u,0x0u}, {0x0u,0x0u}, {0x0u,0x0u}, {0x0u,0x0u}, {0x0u,0x0u}, {0x0u,0x0u}, {0x0u,0x0u}, {0x0u,0x0u},
  {0x10010211u,0x0u}, {0x10010571u,0x0u}, {0x10000f21u,0x0u}, {0x10001171u,0x0u}, {0x10001361u,0x0u}, {0x10001551u,0x0u}, {0x10001741u,0x0u}, {0x10001931u,0x0u}, {0x10001b21u,0x0u}, {0x10001d11u,0x0u}, {0x10001f01u,0x0u}, {0x10020171u,0x0u}, {0x10020461u,0x0u}, {0x10020751u,0x0u}, {0x10020a41u,0x0u}, {0x10020d31u,0x0u}, {0x94d10013u,0x2eaeu}, {0x0u,0x0u},
  {0x10000171u,0x0u}, {0x10000711u,0x0u}, {0x10000c71u,0x0u}, {0x142u,0x0u}, {0xa42u,0x0u}, {0xd52u,0x0u}, {0x1672u,0x0u}, {0x1e02u,0x0u}, {0x1912u,0x0u}, {0xad090173u,0x2eafu}, {0x0u,0x0u}, {0x0u,0x0u}, {0x0u,0x0u}, {0x0u,0x0u}, {0x0u,0x0u}, {0x0u,0x0u}, {0x0u,0x0u}, {0x0u,0x0u},
  {0x10010171u,0x0u}, {0x10000721u,0x0u}, {0x10000d01u,0x0u}, {0x332u,0x0u}, {0x652u,0x0u}, {0xc52u,0x0u}, {0x1772u,0x0u}, {0x1d12u,0x0u}, {0x2e010173u,0x2eacu}, {0x0u,0x0u}, {0x0u,0x0u}, {0x0u,0x0u}, {0x0u,0x0u}, {0x0u,0x0u}, {0x0u,0x0u}, {0x0u,0x0u}, {0x0u,0x0u}, {0x0u,0x0u},
  {0x10010201u,0x0u}, {0x10010561u,0x0u}, {0x10000f31u,0x0u}, {0x10010971u,0x0u}, {0x10001371u,0x0u}, {0x10001561u,0x0u}, {0x10001751u,0x0u}, {0x10001941u,0x0u}, {0x10001b31u,0x0u}, {0x10001d21u,0x0u}, {0x10001f11u,0x0u}, {0x10020201u,0x0u}, {0x10020471u,0x0u}, {0x10020761u,0x0u}, {0x10020a51u,0x0u}, {0x10020d41u,0x0u}, {0x94d50003u,0x2eaeu}, {0x0u,0x0u},
  {0x10010161u,0x0u}, {0x10000731u,0x0u}, {0x10000d11u,0x0u}, {0x232u,0x0u}, {0x552u,0x0u}, {0xb02u,0x0u}, {0x1062u,0x0u}, {0x1b02u,0x0u}, {0x1862u,0x0u}, {0x5e610153u,0x2eadu}, {0x0u,0x0u}, {0x0u,0x0u}, {0x0u,0x0u}, {0x0u,0x0u}, {0x0u,0x0u}, {0x0u,0x0u}, {0x0u,0x0u}, {0x0u,0x0u},
  {0x10010151u,0x0u}, {0x10000741u,0x0u}, {0x10000d21u,0x0u}, {0x132u,0x0u}, {0x952u,0x0u}, {0x1052u,0x0u}, {0x1512u,0x0u}, {0x1702u,0x0u}, {0x1a72u,0x0u}, {0x96e10103u,0x2eaeu}, {0x0u,0x0u}, {0x0u,0x0u}, {0x0u,0x0u}, {0x0u,0x0u}, {0x0u,0x0u}, {0x0u,0x0u}, {0x0u,0x0u}, {0x0u,0x0u},
  {0x10000401u,0x0u}, {0x10010551u,0x0u}, {0x10000f41u,0x0u}, {0x10010961u,0x0u}, {0x10010a71u,0x0u}, {0x10001571u,0x0u}, {0x10001761u,0x0u}, {0x10001951u,0x0u}, {0x10001b41u,0x0u}, {0x10001d31u,0x0u}, {0x10001f21u,0x0u}, {0x10020211u,0x0u}, {0x10020501u,0x0u}, {0x10020771u,0x0u}, {0x10020a61u,0x0u}, {0x10020d51u,0x0u}, {0x66790133u,0x2eadu}, {0x0u,0x0u},
  {0x10010141u,0x0u}, {0x10000751u,0x0u}, {0x10000d31u,0x0u}, {0x432u,0x0u}, {0x852u,0x0u}, {0xc42u,0x0u}, {0x1572u,0x0u}, {0x1e52u,0x0u}, {0xad290113u,0x2eafu}, {0x0u,0x0u}, {0x0u,0x0u}, {0x0u,0x0u}, {0x0u,0x0u}, {0x0u,0x0u}, {0x0u,0x0u}, {0x0u,0x0u}, {0x0u,0x0u}, {0x0u,0x0u},
  {0x10010131u,0x0u}, {0x10000761u,0x0u}, {0x10010631u,0x0u}, {0x10001041u,0x0u}, {0x562u,0x0u}, {0x712u,0x0u}, {0xf02u,0x0u}, {0x1222u,0x0u}, {0x1542u,0x0u}, {0x1b22u,0x0u}, {0x1e22u,0x0u}, {0x68750013u,0x2eadu}, {0x0u,0x0u}, {0x0u,0x0u}, {0x0u,0x0u}, {0x0u,0x0u}, {0x0u,0x0u}, {0x0u,0x0u},
  {0x10000411u,0x0u}, {0x10010541u,0x0u}, {0x10000f51u,0x0u}, {0x10010951u,0x0u}, {0x10010a61u,0x0u}, {0x10010b71u,0x0u}, {0x10001771u,0x0u}, {0x10001961u,0x0u}, {0x10001b51u,0x0u}, {0x10001d41u,0x0u}, {0x10001f31u,0x0u}, {0x10020221u,0x0u}, {0x10020511u,0x0u}, {0x10020801u,0x0u}, {0x10020a71u,0x0u}, {0x10020d61u,0x0u}, {0x70890103u,0x2eadu}, {0x0u,0x0u},
  {0x10010121u,0x0u}, {0x10000771u,0x0u}, {0x10000d41u,0x0u}, {0x32u,0x0u}, {0xb52u,0x0u}, {0xf42u,0x0u}, {0x1472u,0x0u}, {0x1d22u,0x0u}, {0x30010073u,0x2eacu}, {0x0u,0x0u}, {0x0u,0x0u}, {0x0u,0x0u}, {0x0u,0x0u}, {0x0u,0x0u}, {0x0u,0x0u}, {0x0u,0x0u}, {0x0u,0x0u}, {0x0u,0x0u},
  {0x10000421u,0x0u}, {0x10010531u,0x0u}, {0x10000f61u,0x0u}, {0x10010941u,0x0u}, {0x10010a51u,0x0u}, {0x10010b61u,0x0u}, {0x10010c71u,0x0u}, {0x10001971u,0x0u}, {0x10001b61u,0x0u}, {0x10001d51u,0x0u}, {0x10001f41u,0x0u}, {0x10020231u,0x0u}, {0x10020521u,0x0u}, {0x10020811u,0x0u}, {0x10020b01u,0x0u}, {0x10020d71u,0x0u}, {0x86b90053u,0x2eaeu}, {0x0u,0x0u},
  {0x10010111u,0x0u}, {0x10010471u,0x0u}, {0x10000d51u,0x0u}, {0x422u,0x0u}, {0x202u,0x0u}, {0xa52u,0x0u}, {0xe22u,0x0u}, {0x1112u,0x0u}, {0x1552u,0x0u}, {0x1e62u,0x0u}, {0xad1d0043u,0x2eafu}, {0x0u,0x0u}, {0x0u,0x0u}, {0x0u,0x0u}, {0x0u,0x0u}, {0x0u,0x0u}, {0x0u,0x0u}, {0x0u,0x0u},
  {0x10010101u,0x0u}, {0x10010461u,0x0u}, {0x10000d61u,0x0u}, {0x22u,0x0u}, {0x502u,0x0u}, {0x842u,0x0u}, {0x912u,0x0u}, {0xd02u,0x0u}, {0x1272u,0x0u}, {0x1c72u,0x0u}, {0xad1d0133u,0x2eafu}, {0x0u,0x0u}, {0x0u,0x0u}, {0x0u,0x0u}, {0x0u,0x0u}, {0x0u,0x0u}, {0x0u,0x0u}, {0x0u,0x0u},
  {0x10000431u,0x0u}, {0x10010521u,0x0u}, {0x10000f71u,0x0u}, {0x10010931u,0x0u}, {0x10010a41u,0x0u}, {0x10010b51u,0x0u}, {0x10010c61u,0x0u}, {0x10010d71u,0x0u}, {0x10001b71u,0x0u}, {0x10001d61u,0x0u}, {0x10001f51u,0x0u}, {0x10020241u,0x0u}, {0x10020531u,0x0u}, {0x10020821u,0x0u}, {0x10020b11u,0x0u}, {0x3c010133u,0x2eacu}, {0x0u,0x0u}, {0x0u,0x0u},
  {0x10000201u,0x0u}, {0x10010451u,0x0u}, {0x10000d71u,0x0u}, {0x322u,0x0u}, {0x102u,0x0u}, {0x742u,0x0u}, {0x612u,0x0u}, {0xc02u,0x0u}, {0x1372u,0x0u}, {0x1a22u,0x0u}, {0x44010103u,0x2eacu}, {0x0u,0x0u}, {0x0u,0x0u}, {0x0u,0x0u}, {0x0u,0x0u}, {0x0u,0x0u}, {0x0u,0x0u}, {0x0u,0x0u},
  {0x10000211u,0x0u}, {0x10010441u,0x0u}, {0x10000e01u,0x0u}, {0x222u,0x0u}, {0xa62u,0x0u}, {0xe42u,0x0u}, {0x1412u,0x0u}, {0x1622u,0x0u}, {0x1a32u,0x0u}, {0x1f12u,0x0u}, {0x5c5d0053u,0x2eadu}, {0x0u,0x0u}, {0x0u,0x0u}, {0x0u,0x0u}, {0x0u,0x0u}, {0x0u,0x0u}, {0x0u,0x0u}, {0x0u,0x0u},
  {0x10000441u,0x0u}, {0x10010511u,0x0u}, {0x10010871u,0x0u}, {0x10010921u,0x0u}, {0x10010a31u,0x0u}, {0x10010b41u,0x0u}, {0x10010c51u,0x0u}, {0x10010d61u,0x0u}, {0x10010e71u,0x0u}, {0x10001d71u,0x0u}, {0x10001f61u,0x0u}, {0x10020251u,0x0u}, {0x10020541u,0x0u}, {0x10020831u,0x0u}, {0x10020b21u,0x0u}, {0x3e010113u,0x2eacu}, {0x0u,0x0u}, {0x0u,0x0u},
  {0x10000221u,0x0u}, {0x10010431u,0x0u}, {0x10000e11u,0x0u}, {0x122u,0x0u}, {0xb62u,0x0u}, {0xd42u,0x0u}, {0x1312u,0x0u}, {0x1722u,0x0u}, {0x1d72u,0x0u}, {0xad190143u,0x2eafu}, {0x0u,0x0u}, {0x0u,0x0u}, {0x0u,0x0u}, {0x0u,0x0u}, {0x0u,0x0u}, {0x0u,0x0u}, {0x0u,0x0u}, {0x0u,0x0u},
  {0x10000231u,0x0u}, {0x10010421u,0x0u}, {0x10010621u,0x0u}, {0x10001051u,0x0u}, {0x762u,0x0u}, {0xa12u,0x0u}, {0xe02u,0x0u}, {0x1122u,0x0u}, {0x1442u,0x0u}, {0x1c62u,0x0u}, {0x64790033u,0x2eadu}, {0x0u,0x0u}, {0x0u,0x0u}, {0x0u,0x0u}, {0x0u,0x0u}, {0x0u,0x0u}, {0x0u,0x0u}, {0x0u,0x0u},
  {0x10000451u,0x0u}, {0x10010501u,0x0u}, {0x10010861u,0x0u}, {0x10010911u,0x0u}, {0x10010a21u,0x0u}, {0x10010b31u,0x0u}, {0x10010c41u,0x0u}, {0x10010d51u,0x0u}, {0x10010e61u,0x0u}, {0x10010f71u,0x0u}, {0x10001f71u,0x0u}, {0x10020261u,0x0u}, {0x10020551u,0x0u}, {0x10020841u,0x0u}, {0x10020b31u,0x0u}, {0x3c010003u,0x2eacu}, {0x0u,0x0u}, {0x0u,0x0u},
  {0x10000241u,0x0u}, {0x10010411u,0x0u}, {0x10000e21u,0x0u}, {0x312u,0x0u}, {0x772u,0x0u}, {0x1042u,0x0u}, {0x1562u,0x0u}, {0x1d52u,0x0u}, {0xad190153u,0x2eafu}, {0x0u,0x0u}, {0x0u,0x0u}, {0x0u,0x0u}, {0x0u,0x0u}, {0x0u,0x0u}, {0x0u,0x0u}, {0x0u,0x0u}, {0x0u,0x0u}, {0x0u,0x0u},
  {0x10000251u,0x0u}, {0x10010401u,0x0u}, {0x10000e31u,0x0u}, {0x212u,0x0u}, {0x672u,0x0u}, {0xe32u,0x0u}, {0x1352u,0x0u}, {0x1b52u,0x0u}, {0x30010143u,0x2eacu}, {0x0u,0x0u}, {0x0u,0x0u}, {0x0u,0x0u}, {0x0u,0x0u}, {0x0u,0x0u}, {0x0u,0x0u}, {0x0u,0x0u}, {0x0u,0x0u}, {0x0u,0x0u},
  {0x10000461u,0x0u}, {0x10000a01u,0x0u}, {0x10010851u,0x0u}, {0x10010901u,0x0u}, {0x10010a11u,0x0u}, {0x10010b21u,0x0u}, {0x10010c31u,0x0u}, {0x10010d41u,0x0u}, {0x10010e51u,0x0u}, {0x10010f61u,0x0u}, {0x10020001u,0x0u}, {0x10020271u,0x0u}, {0x10020561u,0x0u}, {0x10020851u,0x0u}, {0x10020b41u,0x0u}, {0x3c010123u,0x2eacu}, {0x0u,0x0u}, {0x0u,0x0u},
  {0x10000261u,0x0u}, {0x10000801u,0x0u}, {0x10000e41u,0x0u}, {0x512u,0x0u}, {0x572u,0x0u}, {0xd32u,0x0u}, {0x1342u,0x0u}, {0x1922u,0x0u}, {0x1c42u,0x0u}, {0x8ed10043u,0x2eaeu}, {0x0u,0x0u}, {0x0u,0x0u}, {0x0u,0x0u}, {0x0u,0x0u}, {0x0u,0x0u}, {0x0u,0x0u}, {0x0u,0x0u}, {0x0u,0x0u},
  {0x10000271u,0x0u}, {0x10000811u,0x0u}, {0x10000e51u,0x0u}, {0x412u,0x0u}, {0x972u,0x0u}, {0xc32u,0x0u}, {0x1242u,0x0u}, {0x1822u,0x0u}, {0x1d32u,0x0u}, {0x6c7d0113u,0x2eadu}, {0x0u,0x0u}, {0x0u,0x0u}, {0x0u,0x0u}, {0x0u,0x0u}, {0x0u,0x0u}, {0x0u,0x0u}, {0x0u,0x0u}, {0x0u,0x0u},
  {0x10000471u,0x0u}, {0x10000a11u,0x0u}, {0x10010841u,0x0u}, {0x10001201u,0x0u}, {0x10010a01u,0x0u}, {0x10010b11u,0x0u}, {0x10010c21u,0x0u}, {0x10010d31u,0x0u}, {0x10010e41u,0x0u}, {0x10010f51u,0x0u}, {0x10020011u,0x0u}, {0x10020301u,0x0u}, {0x10020571u,0x0u}, {0x10020861u,0x0u}, {0x10020b51u,0x0u}, {0x3c010023u,0x2eacu}, {0x0u,0x0u}, {0x0u,0x0u},
  {0x10000301u,0x0u}, {0x10000821u,0x0u}, {0x10000e61u,0x0u}, {0x12u,0x0u}, {0x872u,0x0u}, {0xf32u,0x0u}, {0x1232u,0x0u}, {0x1952u,0x0u}, {0x1a12u,0x0u}, {0x6a790023u,0x2eadu}, {0x0u,0x0u}, {0x0u,0x0u}, {0x0u,0x0u}, {0x0u,0x0u}, {0x0u,0x0u}, {0x0u,0x0u}, {0x0u,0x0u}, {0x0u,0x0u},
  {0x10000311u,0x0u}, {0x10000831u,0x0u}, {0x10000e71u,0x0u}, {0x112u,0x0u}, {0x962u,0x0u}, {0xd72u,0x0u}, {0x1642u,0x0u}, {0x1c52u,0x0u}, {0x1e12u,0x0u}, {0x0u,0x0u}, {0x0u,0x0u}, {0x0u,0x0u}, {0x0u,0x0u}, {0x0u,0x0u}, {0x0u,0x0u}, {0x0u,0x0u}, {0x0u,0x0u}, {0x0u,0x0u},
  {0x10000501u,0x0u}, {0x10000a21u,0x0u}, {0x10010831u,0x0u}, {0x10001211u,0x0u}, {0x10001401u,0x0u}, {0x10010b01u,0x0u}, {0x10010c11u,0x0u}, {0x10010d21u,0x0u}, {0x10010e31u,0x0u}, {0x10010f41u,0x0u}, {0x10020021u,0x0u}, {0x10020311u,0x0u}, {0x10020601u,0x0u}, {0x10020871u,0x0u}, {0x10020b61u,0x0u}, {0x3c010033u,0x2eacu}, {0x0u,0x0u}, {0x0u,0x0u},
  {0x10000321u,0x0u}, {0x10000841u,0x0u}, {0x10000f01u,0x0u}, {0x402u,0x0u}, {0x2u,0x0u}, {0x302u,0x0u}, {0x752u,0x0u}, {0x812u,0x0u}, {0x1152u,0x0u}, {0x1972u,0x0u}, {0x1f02u,0x0u}, {0x1e32u,0x0u}, {0x0u,0x0u}, {0x0u,0x0u}, {0x0u,0x0u}, {0x0u,0x0u}, {0x0u,0x0u}, {0x0u,0x0u},
  {0x10000511u,0x0u}, {0x10000a31u,0x0u}, {0x10010821u,0x0u}, {0x10001221u,0x0u}, {0x10001411u,0x0u}, {0x10001601u,0x0u}, {0x10010c01u,0x0u}, {0x10010d11u,0x0u}, {0x10010e21u,0x0u}, {0x10010f31u,0x0u}, {0x10020031u,0x0u}, {0x10020321u,0x0u}, {0x10020611u,0x0u}, {0x10020901u,0x0u}, {0x10020b71u,0x0u}, {0x3a010013u,0x2eacu}, {0x0u,0x0u}, {0x0u,0x0u},
};
const uint32_t h_first[NCLUSTER] = {0x10010071u, 0x10010061u, 0x10000331u, 0x10010051u, 0x10010041u, 0x10000341u, 0x10010031u, 0x10010021u, 0x10000351u, 0x10010011u, 0x10010001u, 0x10000361u, 0x10000001u, 0x10000011u, 0x10000371u, 0x10000021u, 0x10000031u, 0x10010271u, 0x10000041u, 0x10000051u, 0x10010261u, 0x10000061u, 0x10010251u, 0x10000071u, 0x10000101u, 0x10010241u, 0x10000111u, 0x10000121u, 0x10010231u, 0x10000131u, 0x10000141u, 0x10010221u, 0x10000151u, 0x10000161u, 0x10010211u, 0x10000171u, 0x10010171u, 0x10010201u, 0x10010161u, 0x10010151u, 0x10000401u, 0x10010141u, 0x10010131u, 0x10000411u, 0x10010121u, 0x10000421u, 0x10010111u, 0x10010101u, 0x10000431u, 0x10000201u, 0x10000211u, 0x10000441u, 0x10000221u, 0x10000231u, 0x10000451u, 0x10000241u, 0x10000251u, 0x10000461u, 0x10000261u, 0x10000271u, 0x10000471u, 0x10000301u, 0x10000311u, 0x10000501u, 0x10000321u, 0x10000511u};
__constant__ uint8_t c_gorder[16 * 46] = {
  4, 0, 3, 2, 1, 6, 14, 15, 16, 20, 33, 27, 38, 39, 43, 5, 9, 11, 13, 18, 19, 22, 35, 26, 28, 30, 10, 8, 7, 12, 17, 32, 25, 23, 37, 40, 24, 21, 34, 29, 36, 41, 42, 31, 45, 44,
  4, 0, 3, 2, 5, 1, 10, 8, 7, 12, 17, 32, 33, 27, 38, 39, 43, 9, 6, 14, 15, 16, 20, 34, 29, 36, 41, 42, 11, 13, 18, 19, 21, 35, 26, 28, 30, 22, 25, 23, 37, 40, 24, 31, 45, 44,
  0, 5, 1, 3, 9, 8, 14, 16, 32, 34, 22, 40, 31, 41, 2, 4, 6, 11, 15, 17, 20, 35, 37, 39, 29, 28, 10, 7, 12, 13, 18, 21, 23, 38, 24, 42, 27, 19, 33, 36, 26, 43, 25, 44, 45, 30,
  0, 5, 1, 3, 2, 9, 8, 14, 16, 32, 34, 22, 40, 31, 41, 4, 10, 7, 12, 13, 18, 19, 33, 36, 26, 43, 25, 6, 11, 15, 17, 20, 35, 37, 39, 29, 28, 21, 23, 38, 24, 42, 27, 44, 45, 30,
  2, 4, 0, 3, 8, 9, 11, 16, 17, 33, 22, 25, 39, 28, 42, 1, 10, 6, 14, 13, 18, 20, 23, 26, 27, 30, 7, 5, 15, 12, 19, 21, 37, 24, 38, 43, 32, 34, 35, 36, 40, 29, 41, 31, 44, 45,
  2, 4, 0, 3, 1, 10, 5, 15, 17, 34, 35, 36, 40, 29, 41, 8, 9, 11, 16, 32, 20, 23, 26, 27, 30, 7, 6, 14, 12, 19, 21, 37, 24, 38, 43, 13, 18, 33, 22, 25, 39, 28, 42, 31, 44, 45,
  0, 1, 3, 2, 4, 6, 7, 15, 16, 34, 21, 23, 40, 26, 42, 9, 5, 8, 12, 18, 20, 36, 25, 27, 41, 10, 11, 14, 32, 19, 37, 24, 39, 43, 31, 13, 17, 33, 22, 35, 38, 29, 28, 45, 44, 30,
  0, 1, 3, 2, 4, 6, 11, 13, 17, 33, 22, 35, 38, 29, 28, 9, 5, 8, 14, 18, 20, 36, 25, 27, 41, 10, 7, 15, 16, 34, 21, 23, 40, 26, 42, 12, 32, 19, 37, 24, 39, 43, 31, 45, 44, 30,
  2, 4, 3, 7, 5, 9, 16, 33, 20, 36, 38, 27, 43, 1, 0, 8, 6, 11, 15, 34, 18, 35, 40, 25, 41, 31, 10, 14, 12, 19, 21, 22, 39, 26, 28, 13, 17, 32, 37, 23, 24, 42, 29, 30, 44, 45,
  2, 0, 7, 10, 14, 12, 19, 21, 22, 39, 26, 28, 4, 8, 5, 9, 13, 33, 20, 36, 38, 27, 43, 1, 3, 6, 11, 15, 17, 32, 37, 23, 24, 42, 29, 16, 34, 18, 35, 40, 25, 41, 31, 30, 44, 45,
  4, 0, 10, 15, 12, 33, 35, 23, 40, 41, 29, 2, 3, 7, 6, 13, 17, 18, 20, 22, 25, 42, 45, 1, 11, 8, 16, 32, 37, 36, 38, 24, 26, 9, 5, 14, 34, 19, 21, 39, 27, 43, 30, 31, 44, 28,
  4, 0, 10, 5, 14, 34, 19, 21, 39, 27, 43, 30, 2, 7, 9, 8, 16, 32, 37, 36, 38, 24, 26, 3, 1, 11, 6, 15, 12, 33, 35, 23, 40, 41, 29, 13, 17, 18, 20, 22, 25, 42, 45, 31, 44, 28,
  4, 1, 8, 5, 13, 16, 18, 37, 38, 25, 41, 29, 2, 6, 9, 11, 17, 33, 35, 22, 23, 43, 27, 3, 0, 7, 10, 12, 32, 36, 20, 40, 42, 28, 15, 14, 34, 19, 21, 39, 24, 26, 30, 45, 44, 31,
  4, 6, 9, 13, 16, 18, 37, 38, 25, 41, 29, 2, 1, 8, 11, 12, 32, 36, 20, 40, 42, 28, 3, 0, 7, 15, 17, 33, 35, 22, 23, 43, 27, 5, 10, 14, 34, 19, 21, 39, 24, 26, 30, 45, 44, 31,
  4, 1, 3, 10, 12, 16, 19, 20, 38, 42, 43, 31, 2, 0, 7, 11, 13, 17, 35, 21, 22, 25, 28, 8, 6, 14, 33, 34, 36, 39, 23, 41, 29, 5, 9, 15, 32, 18, 37, 40, 24, 26, 27, 45, 44, 30,
  4, 3, 6, 14, 33, 34, 36, 39, 23, 41, 29, 2, 0, 7, 11, 13, 17, 35, 21, 22, 25, 28, 1, 8, 9, 15, 32, 18, 37, 40, 24, 26, 27, 5, 10, 12, 16, 19, 20, 38, 42, 43, 31, 45, 44, 30,
};


constexpr int F_KV = 0;
constexpr int F_Q = 256;
constexpr int F_A3 = 384;
constexpr int F_PART = 768;
constexpr int F_G = 1024;
constexpr int NFLAGS = 1032;
constexpr int FLAG_STRIDE = 8;

__device__ uint32_t g_flags[NFLAGS * FLAG_STRIDE];
__device__ uint32_t g_epoch;
__device__ float2 g_gate[2048];
__device__ __align__(1024) uint8_t g_kvimg[32u * 16u * 2u * 32768u];
__device__ __align__(1024) uint8_t g_aimg[8u * 46u * 2u * 32768u];
__device__ __align__(1024) uint8_t g_part[16u * 4u * 2u * 3u * 16384u];

struct Params {
  CUtensorMap x, c, wq, wuk, wuv, wg, wu, wo, wd;
  const __nv_bfloat16* xp;
  const __nv_bfloat16* gw;
  __nv_bfloat16* out;
  uint32_t first[NCLUSTER];
};

__device__ __forceinline__ uint32_t smem_u32(const void* p) { return (uint32_t)__cvta_generic_to_shared(p); }
__device__ __forceinline__ void mbar_init(uint32_t a, int c) { asm volatile("mbarrier.init.shared::cta.b64 [%0], %1;" ::"r"(a), "r"(c) : "memory"); }
__device__ __forceinline__ void mbar_expect(uint32_t a, uint32_t b) { asm volatile("mbarrier.arrive.expect_tx.shared::cta.b64 _, [%0], %1;" ::"r"(a), "r"(b) : "memory"); }
__device__ __forceinline__ void mbar_arrive(uint32_t a) { asm volatile("mbarrier.arrive.shared::cta.b64 _, [%0];" ::"r"(a) : "memory"); }
__device__ __forceinline__ void mbar_arrive_if(uint32_t a, uint32_t lane, uint32_t n) {
  asm volatile("{\n.reg .pred p;\nsetp.lt.u32 p, %1, %2;\n@p mbarrier.arrive.shared::cta.b64 _, [%0];\n}" ::"r"(a), "r"(lane), "r"(n) : "memory");
}
__device__ __forceinline__ void mbar_arrive_cl_if(uint32_t a, uint32_t lane, uint32_t n) {
  asm volatile("{\n.reg .pred p;\nsetp.lt.u32 p, %1, %2;\n@p mbarrier.arrive.shared::cluster.b64 _, [%0];\n}" ::"r"(a), "r"(lane), "r"(n) : "memory");
}
__device__ __forceinline__ void mbar_wait(uint32_t a, uint32_t p) {
  asm volatile("{\n.reg .pred P;\nW:\nmbarrier.try_wait.parity.shared::cta.b64 P, [%0], %1;\nvote.sync.all.pred P, P, 0xffffffff;\n@!P bra.uni W;\n}" ::"r"(a), "r"(p) : "memory");
}
__device__ __forceinline__ void mbar_wait2(uint32_t a, uint32_t p, uint32_t b, uint32_t q) {
  asm volatile("{\n.reg .pred P, Q;\nW:\nmbarrier.try_wait.parity.shared::cta.b64 P, [%0], %1;\nmbarrier.try_wait.parity.shared::cta.b64 Q, [%2], %3;\nand.pred P, P, Q;\nvote.sync.all.pred P, P, 0xffffffff;\n@!P bra.uni W;\n}" ::"r"(a), "r"(p), "r"(b), "r"(q) : "memory");
}
__device__ __forceinline__ bool mbar_test2(uint32_t a, uint32_t p, uint32_t b, uint32_t q) {
  uint32_t ok;
  asm volatile("{\n.reg .pred P, Q;\nmbarrier.test_wait.parity.shared::cta.b64 P, [%1], %2;\nmbarrier.test_wait.parity.shared::cta.b64 Q, [%3], %4;\nand.pred P, P, Q;\nselp.u32 %0, 1, 0, P;\n}" : "=r"(ok) : "r"(a), "r"(p), "r"(b), "r"(q) : "memory");
  return ok != 0;
}
__device__ __forceinline__ bool mbar_try_long(uint32_t a, uint32_t p) {
  uint32_t ok;
  asm volatile("{\n.reg .pred P;\nmbarrier.try_wait.parity.shared::cta.b64 P, [%1], %2, 2000;\nselp.u32 %0, 1, 0, P;\n}" : "=r"(ok) : "r"(a), "r"(p) : "memory");
  return ok != 0;
}
__device__ __forceinline__ uint32_t mapa(uint32_t a, uint32_t cta) { uint32_t r; asm("mapa.shared::cluster.u32 %0, %1, %2;" : "=r"(r) : "r"(a), "r"(cta)); return r; }

__device__ __forceinline__ void bulk_load(uint32_t dst, const void* src, uint32_t bytes, uint32_t bar) {
  asm volatile("cp.async.bulk.shared::cluster.global.mbarrier::complete_tx::bytes [%0], [%1], %2, [%3];" ::"r"(dst), "l"(src), "r"(bytes), "r"(bar) : "memory");
}
__device__ __forceinline__ void bulk_load_mc(uint32_t dst, const void* src, uint32_t bytes, uint32_t bar) {
  asm volatile("cp.async.bulk.shared::cluster.global.mbarrier::complete_tx::bytes.multicast::cluster [%0], [%1], %2, [%3], %4;" ::"r"(dst), "l"(src), "r"(bytes), "r"(bar), "h"((uint16_t)3) : "memory");
}
__device__ __forceinline__ void tma4(uint32_t dst, const CUtensorMap* m, int c0, int c1, int c2, int c3, uint32_t bar) {
  asm volatile("cp.async.bulk.tensor.4d.shared::cluster.global.mbarrier::complete_tx::bytes [%0], [%1, {%3, %4, %5, %6}], [%2];" ::"r"(dst), "l"(m), "r"(bar), "r"(c0), "r"(c1), "r"(c2), "r"(c3) : "memory");
}
__device__ __forceinline__ void tma3_mc(uint32_t dst, const CUtensorMap* m, int c0, int c1, int c2, uint32_t bar) {
  asm volatile("cp.async.bulk.tensor.3d.shared::cluster.global.mbarrier::complete_tx::bytes.multicast::cluster [%0], [%1, {%3, %4, %5}], [%2], %6;" ::"r"(dst), "l"(m), "r"(bar), "r"(c0), "r"(c1), "r"(c2), "h"((uint16_t)3) : "memory");
}
__device__ __forceinline__ void tma5_mc(uint32_t dst, const CUtensorMap* m, int c0, int c4, uint32_t bar) {
  asm volatile("cp.async.bulk.tensor.5d.shared::cluster.global.mbarrier::complete_tx::bytes.multicast::cluster [%0], [%1, {%3, %4, %4, %4, %5}], [%2], %6;" ::"r"(dst), "l"(m), "r"(bar), "r"(c0), "r"(0), "r"(c4), "h"((uint16_t)3) : "memory");
}
__device__ __forceinline__ uint64_t desc64(uint32_t lo) { return (uint64_t)lo | (0x40000040ull << 32); }
#define WG_FENCE() asm volatile("wgmma.fence.sync.aligned;" ::: "memory")
#define WG_COMMIT() asm volatile("wgmma.commit_group.sync.aligned;" ::: "memory")
#define WG_WAIT(n) asm volatile("wgmma.wait_group.sync.aligned %0;" ::"n"(n) : "memory")

template <int N> __device__ __forceinline__ void reg_fence(float (&a)[N]) {
#pragma unroll
  for (int i = 0; i < N; i++) asm volatile("" : "+f"(a[i])::"memory");
}
template <int N> __device__ __forceinline__ void reg_undef(float (&a)[N]) {
#pragma unroll
  for (int i = 0; i < N; i++) asm volatile("" : "=f"(a[i]));
}
template <int N> __device__ __forceinline__ void reg_fence_u(uint32_t (&a)[N]) {
#pragma unroll
  for (int i = 0; i < N; i++) asm volatile("" : "+r"(a[i])::"memory");
}
__device__ __forceinline__ uint32_t pack_bf16(float lo, float hi) {
  uint32_t r; asm("cvt.rn.bf16x2.f32 %0, %1, %2;" : "=r"(r) : "f"(hi), "f"(lo)); return r;
}
__device__ __forceinline__ float ex2(float x) { float y; asm("ex2.approx.ftz.f32 %0, %1;" : "=f"(y) : "f"(x)); return y; }
__device__ __forceinline__ float tanh_fast(float x) { float y; asm("tanh.approx.f32 %0, %1;" : "=f"(y) : "f"(x)); return y; }
__device__ __forceinline__ void stg128(void* p, uint32_t a, uint32_t b, uint32_t c, uint32_t d) {
  asm volatile("st.global.v4.b32 [%0], {%1, %2, %3, %4};" ::"l"(p), "r"(a), "r"(b), "r"(c), "r"(d) : "memory");
}
__device__ __forceinline__ void bar_sync(int id) { asm volatile("bar.sync %0, 256;" ::"r"(id) : "memory"); }
__device__ __forceinline__ void bar_arrive(int id) { asm volatile("bar.arrive %0, 256;" ::"r"(id) : "memory"); }

__device__ __forceinline__ void dep_wait(uint32_t cnt, uint32_t n) {
  while (true) {
    uint32_t v;
    asm volatile("ld.acquire.cta.shared.u32 %0, [%1];" : "=r"(v) : "r"(cnt) : "memory");
    if (__all_sync(0xffffffffu, v >= n)) break;
    __nanosleep(40);
  }
  asm volatile("fence.proxy.async.global;" ::: "memory");
}
__device__ __forceinline__ void flag_signal(int idx) {
  asm volatile("fence.proxy.async.global;" ::: "memory");
  asm volatile("fence.acq_rel.gpu;" ::: "memory");
  asm volatile("red.relaxed.gpu.global.add.u32 [%0], 1;" ::"l"(&g_flags[idx * FLAG_STRIDE]) : "memory");
}

__device__ __forceinline__ uint2 task_at(int i) {
  uint32_t c;
  asm volatile("mov.u32 %0, %%ctaid.x;" : "=r"(c));
  return c_tasks[(c >> 1) * MAXT + i];
}
__device__ __forceinline__ int opaque(int v) { asm volatile("" : "+r"(v)); return v; }
#define lane_now() opaque(lane)
struct Ring {
  uint32_t s, ph;
  __device__ __forceinline__ void next() { if (++s == NSLOT) { s = 0; ph ^= 1; } }
};

__device__ __forceinline__ void store_tile(const float* a, float s0, float s1, uint8_t* blk0, uint32_t blk_stride, uint32_t toff0, uint32_t toff1) {
#pragma unroll
  for (int t4 = 0; t4 < 4; t4++) {
    uint8_t* b = blk0 + (t4 >> 1) * blk_stride + ((t4 & 1) ? toff1 : toff0);
    const float* v = a + 16 * t4;
    stg128(b, pack_bf16(v[0] * s0, v[1] * s0), pack_bf16(v[4] * s0, v[5] * s0), pack_bf16(v[8] * s0, v[9] * s0), pack_bf16(v[12] * s0, v[13] * s0));
    stg128(b + 1024, pack_bf16(v[2] * s1, v[3] * s1), pack_bf16(v[6] * s1, v[7] * s1), pack_bf16(v[10] * s1, v[11] * s1), pack_bf16(v[14] * s1, v[15] * s1));
  }
}
__device__ __forceinline__ float bf_lo(uint32_t v) { return __uint_as_float(v << 16); }
__device__ __forceinline__ float bf_hi(uint32_t v) { return __uint_as_float(v & 0xffff0000u); }

__device__ __forceinline__ uint32_t scale_q(uint32_t v) {
  uint32_t r;
  asm("{\n.reg .b32 t;\nmul.rn.bf16x2 t, %1, %3;\nfma.rn.bf16x2 %0, %1, %2, t;\n}" : "=r"(r) : "r"(v), "r"(0x3e033e03u), "r"(0xb9d8b9d8u));
  return r;
}
constexpr float SM_LIMIT = 1.8014399e16f;
template <int J0> __device__ __forceinline__ void sm_mask(float (&s)[64], int lim0) {
#pragma unroll
  for (int j = 0; j < 8; j++) {
    if (8 * j > lim0) s[4 * (J0 + j)] = -INFINITY;
    if (8 * j + 1 > lim0) s[4 * (J0 + j) + 1] = -INFINITY;
    if (8 * j > lim0 + 8) s[4 * (J0 + j) + 2] = -INFINITY;
    if (8 * j + 1 > lim0 + 8) s[4 * (J0 + j) + 3] = -INFINITY;
  }
}
__device__ __forceinline__ void sm_rowmax(const float (&s)[64], float& a0, float& a1) {
  float x[4] = {s[0], s[2], s[1], s[3]};
#pragma unroll
  for (int j = 1; j < 16; j++) {
    x[0] = fmaxf(x[0], s[4 * j]); x[1] = fmaxf(x[1], s[4 * j + 2]);
    x[2] = fmaxf(x[2], s[4 * j + 1]); x[3] = fmaxf(x[3], s[4 * j + 3]);
  }
  a0 = fmaxf(x[0], x[2]); a1 = fmaxf(x[1], x[3]);
  a0 = fmaxf(a0, __shfl_xor_sync(0xffffffffu, a0, 1)); a1 = fmaxf(a1, __shfl_xor_sync(0xffffffffu, a1, 1));
  a0 = fmaxf(a0, __shfl_xor_sync(0xffffffffu, a0, 2)); a1 = fmaxf(a1, __shfl_xor_sync(0xffffffffu, a1, 2));
}
template <int J0, int J1, bool FMA> __device__ __forceinline__ void sm_exp(const float (&s)[64], uint32_t (&pf)[32], float sc, float n0, float n1, float& t0, float& t1) {
#pragma unroll
  for (int j = J0; j < J1; j++) {
    const float e0 = ex2(FMA ? fmaf(s[4 * j], sc, n0) : s[4 * j]), e1 = ex2(FMA ? fmaf(s[4 * j + 1], sc, n0) : s[4 * j + 1]);
    const float e2 = ex2(FMA ? fmaf(s[4 * j + 2], sc, n1) : s[4 * j + 2]), e3 = ex2(FMA ? fmaf(s[4 * j + 3], sc, n1) : s[4 * j + 3]);
    t0 += e0 + e1; t1 += e2 + e3;
    pf[2 * j] = pack_bf16(e0, e1); pf[2 * j + 1] = pack_bf16(e2, e3);
  }
}
__device__ __forceinline__ void pin_after(float x, uint32_t dummy) {
  asm volatile("{\n.reg .pred p;\nsetp.eq.f32 p, %0, 0f4640E6B7;\n@p st.shared.u32 [%1], 0;\n}" ::"f"(x), "r"(dummy) : "memory");
}


__device__ __noinline__ void helper_roles(const Params* Pp, const int warp, const uint32_t sbase, const uint32_t rank) {
  const Params& P = *Pp;
  const int lane = threadIdx.x & 31;
  const uint32_t bar_sigf = sbase + SMEM_BAR + 16 * NSLOT;
  const uint32_t bar_sige = bar_sigf + 16;
  const uint32_t bar_done = bar_sige + 16;
  const uint32_t dep_cnt = bar_done + 16;
      if (blockIdx.x < 128) {
        const uint4* gw = reinterpret_cast<const uint4*>(P.gw);
        if (warp == 9 && lane == 0) asm volatile("cp.async.bulk.prefetch.L2.global [%0], 16384;" ::"l"(P.xp + (size_t)blockIdx.x * 16 * 512) : "memory");
        const uint4 w0 = gw[lane], w1 = gw[lane + 32];
#pragma unroll 1
        for (int i = warp - 9; i < 16; i += 6) {
          const int row = blockIdx.x * 16 + i, row2 = blockIdx.x * 16 + min(i + 3, 15);
          const uint4* xr = reinterpret_cast<const uint4*>(P.xp + (size_t)row * 512);
          const uint4* yr = reinterpret_cast<const uint4*>(P.xp + (size_t)row2 * 512);
          const uint4 a0 = xr[lane], a1 = xr[lane + 32], b0 = yr[lane], b1 = yr[lane + 32];
          float s = 0.f, u = 0.f;
          const uint32_t av[8] = {a0.x, a0.y, a0.z, a0.w, a1.x, a1.y, a1.z, a1.w};
          const uint32_t bv[8] = {b0.x, b0.y, b0.z, b0.w, b1.x, b1.y, b1.z, b1.w};
          const uint32_t wv[8] = {w0.x, w0.y, w0.z, w0.w, w1.x, w1.y, w1.z, w1.w};
#pragma unroll
          for (int k = 0; k < 8; k++) {
            const __nv_bfloat162 p = __hmul2(*reinterpret_cast<const __nv_bfloat162*>(&av[k]), *reinterpret_cast<const __nv_bfloat162*>(&wv[k]));
            const __nv_bfloat162 p2 = __hmul2(*reinterpret_cast<const __nv_bfloat162*>(&bv[k]), *reinterpret_cast<const __nv_bfloat162*>(&wv[k]));
            s += __low2float(p) + __high2float(p);
            u += __low2float(p2) + __high2float(p2);
          }
#pragma unroll
          for (int o = 16; o > 0; o >>= 1) { s += __shfl_xor_sync(0xffffffffu, s, o); u += __shfl_xor_sync(0xffffffffu, u, o); }
          if (lane & 1) s = u;
          s = __bfloat162float(__float2bfloat16(s));
          const float g = __bfloat162float(__float2bfloat16(__fdividef(1.f, 1.f + __expf(-s))));
          const float og = __bfloat162float(__float2bfloat16(1.f - g));
          if (lane == 0 || (lane == 1 && i + 3 < 16)) g_gate[lane ? row2 : row] = make_float2(g, 0.5f * og);
        }
        __syncwarp();
        if (lane == 0) flag_signal(F_G);
        __syncwarp();
      }
      if (warp != 9) asm volatile("barrier.cluster.wait.aligned;" ::: "memory");
      if (warp < 11) {
        const int w = warp - 9;
        uint32_t ph = 0;
#pragma unroll 1
        for (int ti = 0; ti < MAXT; ti++) {
          const uint2 t = task_at(ti);
          const int type = t.x & 15;
          if (type == T_END) break;
          const int m = (t.x >> 4) & 15, idx = (t.x >> 8) & 255;
          int f;
          if (type == T_G1) {
            const int kind = (t.x >> 16) & 3;
            f = kind == K_KV ? F_KV + idx * 8 + m : (kind == K_Q ? F_Q + idx * 8 + m : F_A3 + m * 46 + 32 + idx);
          } else if (type == T_ATT) {
            f = F_A3 + m * 46 + idx;
          } else {
            f = F_PART + (((m * 2 + idx) * 2 + rank) * 2 + w) * 4 + (((lane + 1) ^ t.y) & 3);
          }
          while (!mbar_try_long(bar_sigf + 8 * w, ph)) { __nanosleep(20); }
          if (lane == 0) {
            mbar_arrive(bar_sige + 8 * w);
            if (type == T_G1 && (task_at(ti + 1).x & 15) == T_ATT) {
              const uint32_t sl = (12 * (ti + 1) + w) % NSLOT;
              uint8_t* dstp = g_kvimg + (size_t)(idx * 16 + 2 * m + w) * 2 * UNIT + rank * 8192;
#pragma unroll 1
              for (int i = 0; i < 4; i++)
                asm volatile("cp.async.bulk.global.shared::cta.bulk_group [%0], [%1], 8192;" ::"l"(dstp + i * 16384), "r"(sbase + sl * UNIT + i * 8192) : "memory");
              asm volatile("cp.async.bulk.commit_group;\ncp.async.bulk.wait_group.read 0;" ::: "memory");
              const uint32_t eb = sbase + SMEM_BAR + 8 * NSLOT + 8 * sl;
              asm volatile("mbarrier.arrive.shared::cluster.b64 _, [%0], 8;" ::"r"(mapa(eb, 0)) : "memory");
              asm volatile("mbarrier.arrive.shared::cluster.b64 _, [%0], 8;" ::"r"(mapa(eb, 1)) : "memory");
              asm volatile("cp.async.bulk.wait_group 0;" ::: "memory");
            }
          }
          __syncwarp();
          if (lane == 0 || (type == T_P3 && lane < 3)) flag_signal(f);
          __syncwarp();
          ph ^= 1;
        }
        if (lane == 0) mbar_arrive(bar_done);
      } else {
        uint32_t ep;
        asm volatile("ld.relaxed.gpu.global.u32 %0, [%1];" : "=r"(ep) : "l"(&g_epoch) : "memory");
        ep = ep / (uint32_t)NCTA + 1;
        uint32_t ndep = 0, spins = 0;
#pragma unroll 1
        for (int ti = 0; ti < MAXT; ti++) {
          const uint2 t = task_at(ti);
          const int type = t.x & 15;
          if (type == T_END) break;
          const int m = (t.x >> 4) & 15, idx = (t.x >> 8) & 255, kind = (t.x >> 16) & 3;
          if (type == T_G1 && kind != K_FFN) continue;
          const int ga = (t.x >> 19) & 63, n1 = (int)(((t.x >> 25) + 1) >> 1) - ga, la = (t.y >> 2) & 63, ng = type == T_P3 ? n1 + (int)((t.y >> 8) & 63) - la : (type == T_ATT ? m + 1 : 1);
#pragma unroll 1
          for (int d = 0; d < ng;) {
            int f = F_G;
            uint32_t tgt = ep * 4;
            const int e = min(d + lane, ng - 1);
            if (type == T_ATT) f = lane == 31 ? F_Q + (idx >> 1) * 8 + m : F_KV + idx * 8 + e;
            else if (type == T_P3) f = F_A3 + m * 46 + c_gorder[(m * 2 + idx) * 46 + (e < n1 ? ga + e : la + e - n1)];
            if (type == T_G1 || (type == T_ATT && lane == 30)) { f = F_G; tgt = ep * 384; }
            uint32_t v;
            asm volatile("ld.relaxed.gpu.global.u32 %0, [%1];" : "=r"(v) : "l"(&g_flags[f * FLAG_STRIDE]) : "memory");
            const uint32_t open = __ballot_sync(0xffffffffu, (int32_t)(v - tgt) < 0);
            const int n = open == 0 ? min(32, ng - d) : (type == T_ATT && (open >> 30) ? 0 : __ffs(open) - 1);
            if (n == 0) {
              __nanosleep(200);
              if (++spins > 4000000u) __trap();
              continue;
            }
            asm volatile("fence.acq_rel.gpu;" ::: "memory");
            __syncwarp();
            d += n; ndep += n;
            if (lane == 0) asm volatile("st.release.cta.shared.u32 [%0], %1;" ::"r"(dep_cnt), "r"(ndep) : "memory");
          }
        }
        if (sbase & 1023) __trap();
        while (!mbar_try_long(bar_done, 0)) { __nanosleep(20); if (++spins > 4000000u) __trap(); }
      }
}

__global__ void __cluster_dims__(2, 1, 1) __launch_bounds__(384, 1) mega_kernel(const __grid_constant__ Params P) {
  extern __shared__ __align__(1024) uint8_t smem_raw[];
  const uint32_t sbase = smem_u32(smem_raw);
  const uint32_t bar_full = sbase + SMEM_BAR;
  const uint32_t bar_empty = bar_full + 8 * NSLOT;
  const uint32_t bar_sigf = bar_empty + 8 * NSLOT;
  const uint32_t bar_sige = bar_sigf + 16;
  const uint32_t bar_done = bar_sige + 16;
  const uint32_t dep_cnt = bar_done + 16;
  uint32_t rank;
  asm volatile("mov.u32 %0, %%cluster_ctarank;" : "=r"(rank));
  const int warp = __shfl_sync(0xffffffffu, threadIdx.x >> 5, 0);
  const int lane = threadIdx.x & 31;

  const uint2 t_first = make_uint2(P.first[blockIdx.x >> 1], 0u);
  if (warp == 9) {
    if (lane == 0) {
      mbar_init(bar_done, 11);
      asm volatile("st.shared.u32 [%0], 0;" ::"r"(dep_cnt) : "memory");
#pragma unroll
      for (int i = 0; i < NSLOT; i++) { mbar_init(bar_full + 8 * i, 1); mbar_init(bar_empty + 8 * i, 16); }
#pragma unroll
      for (int i = 0; i < 2; i++) { mbar_init(bar_sigf + 8 * i, 4); mbar_init(bar_sige + 8 * i, 1); }
      asm volatile("fence.mbarrier_init.release.cluster;\nfence.acq_rel.cta;" ::: "memory");
    }
    __syncwarp();
    asm volatile("barrier.cluster.arrive.relaxed.aligned;" ::: "memory");
    const bool kv = ((t_first.x >> 16) & 3) == K_KV;
    const int idx = (t_first.x >> 8) & 255;
#pragma unroll
    for (int sl = 0; sl < 7; sl++) {
      if (lane == 0) {
        if (sl == 0) asm volatile("fence.proxy.async.shared::cta;" ::: "memory");
        mbar_expect(bar_full + 8 * sl, UNIT);
        const int g = sl / 3;
        if (sl % 3 == 0) tma4(sbase + sl * UNIT, kv ? &P.c : &P.x, 0, 64 * rank, 2 * g, 2 * ((t_first.x >> 4) & 15), bar_full + 8 * sl);
        else tma3_mc(sbase + sl * UNIT + rank * 16384, kv ? (rank ? &P.wuv : &P.wuk) : &P.wq, 0, g * 128 + (sl % 3 - 1) * 64, kv ? idx * 2 : idx * 4 + rank * 2, bar_full + 8 * sl);
      }
      if (sl == 0) {
        __syncwarp();
        asm volatile("barrier.cluster.wait.aligned;" ::: "memory");
      }
    }
    __syncwarp();
  } else {
    asm volatile("barrier.cluster.arrive.relaxed.aligned;" ::: "memory");
    if (warp == 10 && lane < 9) asm volatile("prefetch.tensormap [%0];" ::"l"(&P.x + lane) : "memory");
  }

  if (warp < 8) {
    asm volatile("setmaxnreg.inc.sync.aligned.u32 232;");
    const int wg = warp >> 2;
    const int wq = warp & 3;
#define THREAD_CONSTS() const int ln_ = lane_now(); const int r0 = ln_ >> 2, q = ln_ & 3; \
    const uint32_t toff0 = (16 * wq + r0) * 128 + ((q ^ r0) << 4); const uint32_t toff1 = toff0 ^ 64; (void)toff1; (void)toff0
    const uint32_t rel_base = mapa(bar_empty, lane & 1);
    Ring r{0, 0};
    uint32_t sig_ph = 1;
    int first = 0;
    if (wg == 1) bar_arrive(1);
#define RELEASE(slot) mbar_arrive_cl_if(rel_base + 8 * (slot), lane, 2)
#define SIGNAL() do { mbar_wait(bar_sige + 8 * wg, sig_ph); sig_ph ^= 1; asm volatile("fence.acq_rel.cta;" ::: "memory"); __syncwarp(); mbar_arrive_if(bar_sigf + 8 * wg, lane, 1); } while (0)

#define RELEASE_AFTER_WAIT(x, y) do { WG_WAIT(0); reg_fence(acc); RELEASE(x); RELEASE(y); } while (0)
#define NEXT_UNIT(var) const uint32_t var = r.s; mbar_wait(bar_full + 8 * r.s, r.ph); r.next()
    const uint32_t dbase = (sbase & 0x3FFFF) >> 4;
    int ti = 0, sig_carry = 0;
    uint2 t = t_first;
    while (true) {
      const int type = t.x & 15;
      if (type == T_END) break;
      if (type == T_ATT) {
        uint32_t qf[32], pf[32];
        float o[64], s[64];
        reg_undef(s);
        float n0 = 0.f, n1 = 0.f, l0 = 1.f, l1 = 1.f;
#define QK(kk0, kk1) _Pragma("unroll") for (int kk = kk0; kk < kk1; kk++) wgmma_rs_n128(s, qf[4 * kk], qf[4 * kk + 1], qf[4 * kk + 2], qf[4 * kk + 3], desc64(dk + (kk >> 2) * 1024 + (kk & 3) * 2), kk != 0)
#define PV(kk0, kk1) _Pragma("unroll") for (int kk = kk0; kk < kk1; kk++) wgmma_rs_n128_tb(o, pf[4 * kk], pf[4 * kk + 1], pf[4 * kk + 2], pf[4 * kk + 3], desc64(dv + kk * 128), kk != 0 || keep_o)
#pragma unroll
        for (int j = 0; j < 64; j++) o[j] = 0.f;
#pragma unroll
        for (int j = 0; j < 32; j++) pf[j] = 0;
        int role = (wg == first) ? 1 : 0;
        int left = 2 * ((t.x >> 4) & 15) + 1 + role;
        int fresh = 1;
        int prev_x = -1;
        int store_pending = 0, sig_pending = sig_carry, keep_o = 0, prev_half = 1, shifted = 0;
        float f0 = 0.f, f1 = 0.f, g0 = 0.f, g1 = 0.f;
        uint8_t* dstp = nullptr;
        uint32_t sq, sk, sv, pk_, pv_;
#define LOAD_Q(rl) do { \
          const uint32_t l_ = lane_now(); \
          const uint32_t a_ = sbase + sq * UNIT + (rl) * 16384 + (16 * wq + (l_ & 15)) * 128; \
          _Pragma("unroll") for (int kk = 0; kk < 8; kk++) { \
            const uint32_t ad = a_ + (kk >> 2) * 8192 + ((((kk & 3) * 2 + (l_ >> 4)) ^ (l_ & 7)) << 4); \
            asm volatile("ldmatrix.sync.aligned.m8n8.x4.shared.b16 {%0, %1, %2, %3}, [%4];" : "=r"(qf[4 * kk]), "=r"(qf[4 * kk + 1]), "=r"(qf[4 * kk + 2]), "=r"(qf[4 * kk + 3]) : "r"(ad) : "memory"); \
          } } while (0)
        first ^= 1;
        { NEXT_UNIT(s_); sq = s_; }
        LOAD_Q(role);
        { NEXT_UNIT(s_); sk = s_; sv = s_; }
#pragma unroll 1
        while (true) {
          const uint32_t dk = dbase + sk * (UNIT >> 4) + (1u << 16);
          const uint32_t dv = dbase + sv * (UNIT >> 4) + (1024u << 16);
          bar_sync(1 + wg);
          const bool half = left == 1 && (role ^ rank) == 0;
          WG_FENCE();
          QK(0, 8);
          WG_COMMIT();
          if (store_pending) {
            THREAD_CONSTS();
            store_tile(o, f0, f1, dstp, 8192, toff0, toff1);
            reg_fence(o);
          }
          if (prev_half) {
            WG_FENCE();
            PV(0, 4);
            WG_COMMIT();
          } else {
            WG_FENCE();
            PV(0, 8);
            WG_COMMIT();
          }
          bar_arrive(1 + (wg ^ 1));
          prev_half = half;
          if (sig_pending) SIGNAL();
          sig_pending = store_pending;
          store_pending = 0;
          keep_o = 1;
          left--;
          const uint32_t sv_cur = sv;
          WG_WAIT(1);
          reg_fence(s);
          if (sk != sv_cur) RELEASE(sk);
          if (left == 0) {
            const int l_ = lane_now();
            const int lim = 16 * wq + (l_ >> 2) - 2 * (l_ & 3);
            if (half) {
              sm_mask<0>(s, lim);
#pragma unroll
              for (int j = 32; j < 64; j++) s[j] = -INFINITY;
            } else {
              sm_mask<8>(s, lim);
            }
          }
          if (fresh) {
            RELEASE(sq);
            float a0 = fmaxf(fmaxf(s[0], s[1]), fmaxf(s[4], s[5])), a1 = fmaxf(fmaxf(s[2], s[3]), fmaxf(s[6], s[7]));
            a0 = fmaxf(a0, __shfl_xor_sync(0xffffffffu, a0, 1)); a1 = fmaxf(a1, __shfl_xor_sync(0xffffffffu, a1, 1));
            l0 += __shfl_xor_sync(0xffffffffu, l0, 1); l1 += __shfl_xor_sync(0xffffffffu, l1, 1);
            a0 = fmaxf(a0, __shfl_xor_sync(0xffffffffu, a0, 2)); a1 = fmaxf(a1, __shfl_xor_sync(0xffffffffu, a1, 2));
            l0 += __shfl_xor_sync(0xffffffffu, l0, 2); l1 += __shfl_xor_sync(0xffffffffu, l1, 2);
            shifted = __any_sync(0xffffffffu, !(fabsf(a0) <= 24.f && fabsf(a1) <= 24.f));
            n0 = shifted ? -a0 : 0.f; n1 = shifted ? -a1 : 0.f;
            f0 = __fdividef(g0, l0); f1 = __fdividef(g1, l1);
            l0 = 0.f; l1 = 0.f;
            keep_o = 0;
            if (prev_x >= 0) {
              store_pending = 1;
              dstp = g_aimg + (size_t)((((prev_x >> 4) & 15) * 46 + ((prev_x >> 8) & 255)) * 2 + (rank ^ role ^ 1)) * UNIT + (role ^ 1) * 16384;
              if (role) { NEXT_UNIT(sx); RELEASE(sx); }
            }
            fresh = 0;
          }
          if (left == 0) {
            const int row = 256 * ((t.x >> 4) & 15) + 128 * role + 64 * (rank ^ role) + 16 * wq + (lane_now() >> 2);
            g0 = __ldcg(&g_gate[row]).x; g1 = __ldcg(&g_gate[row + 8]).x;
            prev_x = t.x & 0xffff;
            t = task_at(++ti);
            if (!role) {
              { NEXT_UNIT(sx); RELEASE(sx); }
              sv = r.s; pv_ = r.ph; r.next();
            }
            if ((t.x & 15) == T_ATT) {
              first ^= 1;
              { NEXT_UNIT(s_); sq = s_; }
              LOAD_Q(role ^ 1);
              sk = r.s; pk_ = r.ph; r.next();
              left = 2 * ((t.x >> 4) & 15) + 1 + (role ^ 1);
              fresh = 1;
            }
            if (role) { sv = r.s; pv_ = r.ph; r.next(); }
            if (!fresh) { sk = sv; pk_ = pv_; }
            role ^= 1;
          } else {
            sk = r.s; pk_ = r.ph; r.next();
            sv = r.s; pv_ = r.ph; r.next();
          }
          if (shifted) {
#pragma unroll
            for (int j = 0; j < 16; j++) { s[4 * j] += n0; s[4 * j + 1] += n0; s[4 * j + 2] += n1; s[4 * j + 3] += n1; }
          }
          float t0 = 0.f, t1 = 0.f;
          float pe[4 * EXP_SPLIT];
#pragma unroll
          for (int j = 0; j < EXP_SPLIT; j++) {
            pe[4 * j] = ex2(s[4 * j]); pe[4 * j + 1] = ex2(s[4 * j + 1]); pe[4 * j + 2] = ex2(s[4 * j + 2]); pe[4 * j + 3] = ex2(s[4 * j + 3]);
            t0 += pe[4 * j] + pe[4 * j + 1]; t1 += pe[4 * j + 2] + pe[4 * j + 3];
          }
          pin_after(t0 + t1, bar_done + 8);
          WG_WAIT(0);
          reg_fence(o); reg_fence_u(pf); reg_fence(pe); reg_fence(s);
          RELEASE(sv_cur);
#pragma unroll
          for (int j = 0; j < 2 * EXP_SPLIT; j++) pf[j] = pack_bf16(pe[2 * j], pe[2 * j + 1]);
          const bool ok = mbar_test2(bar_full + 8 * sk, pk_, bar_full + 8 * sv, pv_);
          sm_exp<EXP_SPLIT, 8, false>(s, pf, 0.f, 0.f, 0.f, t0, t1);
          if (!half) sm_exp<8, 16, false>(s, pf, 0.f, 0.f, 0.f, t0, t1);
          const bool small = t0 <= SM_LIMIT && t1 <= SM_LIMIT;
          if (!__all_sync(0xffffffffu, ok && small)) {
            if (__any_sync(0xffffffffu, !small)) {
              float a0, a1;
              sm_rowmax(s, a0, a1);
              a0 = fmaxf(a0, 0.f); a1 = fmaxf(a1, 0.f);
              const float c0 = ex2(-a0), c1 = ex2(-a1);
              n0 -= a0; n1 -= a1;
              shifted = 1;
              l0 *= c0; l1 *= c1;
              if (keep_o) {
#pragma unroll
                for (int j = 0; j < 16; j++) { o[4 * j] *= c0; o[4 * j + 1] *= c0; o[4 * j + 2] *= c1; o[4 * j + 3] *= c1; }
              }
              t0 = 0.f; t1 = 0.f;
              sm_exp<0, 16, true>(s, pf, 1.f, -a0, -a1, t0, t1);
            }
            mbar_wait(bar_full + 8 * sk, pk_);
            mbar_wait(bar_full + 8 * sv, pv_);
          }
          l0 += t0; l1 += t1;
          if (left == 0) break;
        }
        {
          const uint32_t dv = dbase + sv * (UNIT >> 4) + (1024u << 16);
          bar_sync(1 + wg);
          if (!prev_half) {
            WG_FENCE();
            PV(4, 8);
            WG_COMMIT();
          }
          WG_FENCE();
          PV(0, 4);
          WG_COMMIT();
          l0 += __shfl_xor_sync(0xffffffffu, l0, 1); l1 += __shfl_xor_sync(0xffffffffu, l1, 1);
          l0 += __shfl_xor_sync(0xffffffffu, l0, 2); l1 += __shfl_xor_sync(0xffffffffu, l1, 2);
          f0 = __fdividef(g0, l0); f1 = __fdividef(g1, l1);
          dstp = g_aimg + (size_t)((((prev_x >> 4) & 15) * 46 + ((prev_x >> 8) & 255)) * 2 + (rank ^ role ^ 1)) * UNIT + (role ^ 1) * 16384;
          WG_WAIT(1);
          bar_arrive(1 + (wg ^ 1));
          WG_WAIT(0);
          reg_fence(o);
          RELEASE(sv);
          if (role) { NEXT_UNIT(sx); RELEASE(sx); }
          THREAD_CONSTS();
          store_tile(o, f0, f1, dstp, 8192, toff0, toff1);
          sig_carry = 1;
        }
        continue;
      }
      {
        float acc[128];
        uint32_t pk[64];
#pragma unroll
        for (int i = 0; i < 128; i++) acc[i] = 0.f;
#pragma unroll
        for (int i = 0; i < 64; i++) pk[i] = 0;
        int pkind = -1;
        uint8_t* p0 = nullptr;
        uint32_t pstride = 0, pdelta = 0;
        float ps0 = 0.f, ps1 = 0.f, pn0 = 0.f, pn1 = 0.f;
        int ty = type;
        if (ti == 0) asm volatile("barrier.cluster.wait.aligned;" ::: "memory");
#pragma unroll 1
        do {
          const int skip0 = (t.x >> 18) & 1, skip1 = (t.x >> 25) & 1;
          const int ng = (int)(((t.x >> 25) + 1) >> 1) - (int)((t.x >> 19) & 63);
          uint32_t prevB = 0, sa = 0, started = 0;
#define MMA_HALF(HF) \
              const uint32_t da = dbase + sa * (UNIT >> 4) + (wg * 2 + HF) * 512 + (1u << 16); \
              const uint32_t db = dbase + sb * (UNIT >> 4) + (512u << 16); \
              if (last) bar_sync(1 + wg);        \
              WG_FENCE(); \
              wgmma_ss_n256_tb(acc, desc64(da), desc64(db), started); \
              _Pragma("unroll") for (int kk = 1; kk < 4; kk++) wgmma_ss_n256_tb(acc, desc64(da + kk * 2), desc64(db + kk * 128), 1); \
              WG_COMMIT(); \
              WG_WAIT(1); \
              if (last) bar_arrive(1 + (wg ^ 1)); \
              mbar_arrive_cl_if(rel_base + 8 * prevB, lane, started); \
              prevB = sb
#define PICK(b) _Pragma("unroll") for (int i = 0; i < 4; i++) { \
                  asm volatile("mov.b32 %0, %1;" : "=r"(v[i]) : "r"(pk[(b) + 2 * i])); \
                  asm volatile("mov.b32 %0, %1;" : "=r"(v[4 + i]) : "r"(pk[32 + (b) + 2 * i])); }
#define GEGLU(b, HF) { \
                asm volatile("" : "+r"(pk[b]), "+r"(pk[(b) + 2]), "+r"(pk[(b) + 4]), "+r"(pk[(b) + 6]), "+r"(pk[(b) + 32]), "+r"(pk[(b) + 34]), "+r"(pk[(b) + 36]), "+r"(pk[(b) + 38])); \
                const float sc = HF ? ps1 : ps0; \
                float x[8], z[8]; \
                _Pragma("unroll") for (int i = 0; i < 4; i++) { x[2 * i] = bf_lo(pk[(b) + 2 * i]); x[2 * i + 1] = bf_hi(pk[(b) + 2 * i]); } \
                _Pragma("unroll") for (int i = 0; i < 8; i++) z[i] = tanh_fast(x[i] * fmaf(0.0356774081363001f * x[i], x[i], 0.7978845608028654f)); \
                _Pragma("unroll") for (int i = 0; i < 4; i++) { x[2 * i] *= bf_lo(pk[32 + (b) + 2 * i]) * sc; x[2 * i + 1] *= bf_hi(pk[32 + (b) + 2 * i]) * sc; } \
                stg128(p0 + HF * 1024, pack_bf16(fmaf(x[0], z[0], x[0]), fmaf(x[1], z[1], x[1])), pack_bf16(fmaf(x[2], z[2], x[2]), fmaf(x[3], z[3], x[3])), \
                       pack_bf16(fmaf(x[4], z[4], x[4]), fmaf(x[5], z[5], x[5])), pack_bf16(fmaf(x[6], z[6], x[6]), fmaf(x[7], z[7], x[7]))); }
#define DRAIN(HF) \
            if (pkind == K_FFN) { \
              if (g & 2) { if (g & 1) GEGLU(24 + HF, HF) else GEGLU(16 + HF, HF) } else { if (g & 1) GEGLU(8 + HF, HF) else GEGLU(HF, HF) } \
            } else if (pkind >= 0) { \
              uint32_t v[8]; \
              if (g & 2) { if (g & 1) { PICK(24 + HF); } else { PICK(16 + HF); } } else { if (g & 1) { PICK(8 + HF); } else { PICK(HF); } } \
              if (pkind == K_Q) { _Pragma("unroll") for (int i = 0; i < 8; i++) v[i] = scale_q(v[i]); } \
              stg128(p0 + pdelta + HF * 1024, v[4], v[5], v[6], v[7]); \
              stg128(p0 + HF * 1024, v[0], v[1], v[2], v[3]); \
            }
#pragma unroll 1
          for (int g = 0; g < ng; g++) {
            const uint32_t prevA = sa;
            sa = r.s;
            const uint32_t pa_ = r.ph;
            r.next();
            if (g > 0 || !skip0) {
              const uint32_t sb = r.s;
              mbar_wait2(bar_full + 8 * sa, pa_, bar_full + 8 * sb, r.ph);
              r.next();
              const bool last = skip1 && g == ng - 1;
              MMA_HALF(0);
              mbar_arrive_cl_if(rel_base + 8 * prevA, lane, started);
              started = 2;
            } else {
              mbar_wait(bar_full + 8 * sa, pa_);
            }
            DRAIN(0);
            if (g < ng - 1 || !skip1) {
              NEXT_UNIT(sb);
              const bool last = g == ng - 1;
              MMA_HALF(1);
              started = 2;
            }
            DRAIN(1);
            if (pkind >= 0) {
              p0 = reinterpret_cast<uint8_t*>(reinterpret_cast<uintptr_t>(p0) ^ 64) + ((g & 1) ? pstride : 0);
              if (g == 3) { sig_carry = 1; pkind = -1; }
            }
            if (sig_carry) { SIGNAL(); sig_carry = 0; }
            if (g == 1 && ((t.x >> 16) & 3) == K_FFN) {
              const int row = 256 * ((t.x >> 4) & 15) + 128 * wg + 64 * rank + 16 * wq + (lane_now() >> 2);
              pn0 = __ldcg(&g_gate[row]).y; pn1 = __ldcg(&g_gate[row + 8]).y;
            }
          }
          if (ty == T_P3) { RELEASE_AFTER_WAIT(prevB, sa); break; }
          const int m = (t.x >> 4) & 15, idx = (t.x >> 8) & 255;
          THREAD_CONSTS();
          pkind = (t.x >> 16) & 3;
          pstride = 8192;
          if (pkind == K_KV) {
            p0 = g_kvimg + (size_t)(idx * 16 + 2 * m + wg) * 2 * UNIT + rank * 8192 + toff0;
            pdelta = UNIT; pstride = 16384;
          } else if (pkind == K_Q) {
            p0 = g_aimg + (size_t)((m * 46 + idx * 2) * 2 + rank) * UNIT + wg * 16384 + toff0;
            pdelta = 2 * UNIT;
          } else {
            ps0 = pn0; ps1 = pn1;
            p0 = g_aimg + (size_t)((m * 46 + 32 + idx) * 2 + rank) * UNIT + wg * 16384 + toff0;
          }
          RELEASE_AFTER_WAIT(prevB, sa);
#pragma unroll
          for (int i = 0; i < 64; i++) pk[i] = pack_bf16(acc[2 * i], acc[2 * i + 1]);
          t = task_at(++ti);
          ty = t.x & 15;
        } while (ty == T_G1 || ty == T_P3);
        if (ty != T_P3) {
          Ring r2 = r;
          if (wg) r2.next();
          mbar_wait(bar_full + 8 * r2.s, r2.ph);
          r.next(); r.next();
          THREAD_CONSTS();
#pragma unroll
          for (int c = 0; c < 16; c++) {
            const int b = 8 * (c >> 1) + (c & 1);
            asm volatile("st.shared.v4.b32 [%0], {%1, %2, %3, %4};" ::"r"(sbase + r2.s * UNIT + ((c & 2) ? toff1 : toff0) + (c >> 2) * 8192 + (c & 1) * 1024),
                         "r"(pk[b]), "r"(pk[b + 2]), "r"(pk[b + 4]), "r"(pk[b + 6]) : "memory");
          }
          asm volatile("fence.proxy.async.shared::cta;" ::: "memory");
          SIGNAL();
          continue;
        }
        const int m = (t.x >> 4) & 15, nh = (t.x >> 8) & 255, qd = t.y & 3;
        const int n2 = (int)((t.y >> 8) & 63) - (int)((t.y >> 2) & 63);
        {
          uint8_t* pb = g_part + (size_t)(((m * 2 + nh) * 4 * 2 + rank) * 3 * 2 + wg) * 8192 + (wq * 32 + lane_now()) * 16;
          uint32_t* flag = &g_flags[(F_PART + (((m * 2 + nh) * 2 + rank) * 2 + wg) * 4) * FLAG_STRIDE];
          uint32_t tgt;
          asm volatile("ld.relaxed.gpu.global.u32 %0, [%1];" : "=r"(tgt) : "l"(&g_epoch) : "memory");
#pragma unroll
          for (int p = 1; p < 4; p++) {
            uint8_t* d = pb + (size_t)((p ^ qd) * 2 * 3 * 2 + (p - 1) * 2) * 8192;
#pragma unroll
            for (int i = 0; i < 4; i++) {
              const float* v = acc + 32 * p + 8 * i;
              stg128(d + i * 2048, pack_bf16(v[0], v[1]), pack_bf16(v[2], v[3]), pack_bf16(v[4], v[5]), pack_bf16(v[6], v[7]));
            }
          }
          SIGNAL();
          tgt = (tgt / (uint32_t)NCTA + 1) * 3;
          float (&ac)[32] = *reinterpret_cast<float (*)[32]>(&acc[0]);
          uint32_t x[48];
#define LATE_GROUP() { \
              const uint32_t sa = r.s, ph_a = r.ph; \
              r.next(); \
              const uint32_t sb = r.s; \
              mbar_wait2(bar_full + 8 * sa, ph_a, bar_full + 8 * sb, r.ph); \
              r.next(); \
              const uint32_t da = dbase + sa * (UNIT >> 4) + (wg * 2) * 512 + (1u << 16); \
              const uint32_t db = dbase + sb * (UNIT >> 4) + (512u << 16); \
              WG_FENCE(); \
              _Pragma("unroll") for (int kk = 0; kk < 8; kk++) wgmma_ss_n64_tb(ac, desc64(da + (kk >> 2) * 512 + (kk & 3) * 2), desc64(db + kk * 128), 1); \
              WG_COMMIT(); }
#define FETCH_PARTIALS() _Pragma("unroll") for (int i = 0; i < 12; i++) \
              asm volatile("ld.relaxed.gpu.global.v4.u32 {%0, %1, %2, %3}, [%4];" : "=r"(x[4 * i]), "=r"(x[4 * i + 1]), "=r"(x[4 * i + 2]), "=r"(x[4 * i + 3]) \
                           : "l"(pb + (size_t)(qd * 2 * 3 * 2 + (i >> 2) * 2) * 8192 + (i & 3) * 2048) : "memory")
#pragma unroll 1
          for (int it = 1; it < n2; it++) LATE_GROUP();
          uint32_t v;
          asm volatile("ld.acquire.gpu.global.u32 %0, [%1];" : "=r"(v) : "l"(flag + qd * FLAG_STRIDE) : "memory");
          if (__all_sync(0xffffffffu, (int32_t)(v - tgt) >= 0)) {
            FETCH_PARTIALS();
            LATE_GROUP();
          } else {
            LATE_GROUP();
            asm volatile("{\n.reg .pred p;\n.reg .u32 v;\nW:\nld.acquire.gpu.global.u32 v, [%0];\nsub.u32 v, v, %1;\nsetp.ge.s32 p, v, 0;\nvote.sync.all.pred p, p, 0xffffffff;\n@!p bra.uni W;\n}" ::"l"(flag + qd * FLAG_STRIDE), "r"(tgt) : "memory");
            FETCH_PARTIALS();
          }
          WG_WAIT(0);
          reg_fence(ac);
#pragma unroll
          for (int i = 0; i < 48; i++) { ac[2 * (i & 15)] += bf_lo(x[i]); ac[2 * (i & 15) + 1] += bf_hi(x[i]); }
          THREAD_CONSTS();
          __nv_bfloat16* o = P.out + (size_t)(256 * m + 128 * wg + 64 * rank + 16 * wq + r0) * 512 + nh * 256 + qd * 64 + 8 * q;
#pragma unroll
          for (int c = 0; c < 4; c++) {
            const int b = 16 * (c >> 1) + 2 * (c & 1);
            uint32_t v0 = pack_bf16(ac[b], ac[b + 1]), v1 = pack_bf16(ac[b + 4], ac[b + 5]), v2 = pack_bf16(ac[b + 8], ac[b + 9]), v3 = pack_bf16(ac[b + 12], ac[b + 13]);
            const bool o1 = q & 1, o2 = q & 2;
            uint32_t e0 = o1 ? v0 : v1, e1 = o1 ? v2 : v3;
            e0 = __shfl_xor_sync(0xffffffffu, e0, 1); e1 = __shfl_xor_sync(0xffffffffu, e1, 1);
            if (o1) { v0 = e0; v2 = e1; } else { v1 = e0; v3 = e1; }
            e0 = o2 ? v0 : v2; e1 = o2 ? v1 : v3;
            e0 = __shfl_xor_sync(0xffffffffu, e0, 2); e1 = __shfl_xor_sync(0xffffffffu, e1, 2);
            if (o2) { v0 = e0; v1 = e1; } else { v2 = e0; v3 = e1; }
            stg128(o + (c & 1) * 8 * 512 + (c >> 1) * 32, v0, v1, v2, v3);
          }
        }
        break;
      }
    }
    if (sig_carry) SIGNAL();
    mbar_arrive_if(bar_done, lane, 1);
    asm volatile("barrier.cluster.arrive.relaxed.aligned;\nbarrier.cluster.wait.aligned;" ::: "memory");
  } else {
    asm volatile("setmaxnreg.dec.sync.aligned.u32 40;");
    if (warp != 8) {
      helper_roles(&P, warp, sbase, rank);
    } else {
      Ring r{0, 1};
      uint32_t ndep = 0;
      const uint8_t* pend_v = nullptr;
      const bool el = lane == 0;
#define ACQ(bytes) mbar_wait(bar_empty + 8 * r.s, r.ph); const uint32_t dst = sbase + r.s * UNIT, fb = bar_full + 8 * r.s; r.next(); if (el) mbar_expect(fb, bytes)
#pragma unroll 1
      for (int ti = 0; ti < MAXT; ti++) {
        const uint2 t = task_at(ti);
        const int type = t.x & 15;
        if (type == T_END) break;
        const int m = (t.x >> 4) & 15, idx = (t.x >> 8) & 255, kind = (t.x >> 16) & 3;
        if (type == T_ATT) {
          const int h = idx, n = 2 * m + 2;
          if ((task_at(ti - 1).x & 15) == T_G1) {
#pragma unroll 1
            for (int u = 0; u < 2; u++) { ACQ(0); (void)dst; }
          }
          dep_wait(dep_cnt, ++ndep);
          {
            ACQ(UNIT);
            if (el) {
              bulk_load(dst, g_aimg + ((size_t)((m * 46 + h) * 2 + rank)) * UNIT, UNIT / 2, fb);
              bulk_load(dst + UNIT / 2, g_aimg + ((size_t)((m * 46 + h) * 2 + (rank ^ 1))) * UNIT + UNIT / 2, UNIT / 2, fb);
            }
          }
          const uint8_t* kb = g_kvimg + (size_t)h * 32 * UNIT + rank * 16384;
          const int nu = (task_at(ti + 1).x & 15) == T_ATT ? 2 * n : 2 * n + 2;
#pragma unroll 1
          for (int u = 0; u < nu; u++) {
            const uint8_t* src = (u & 1) ? pend_v : (u < 2 * n ? kb + (size_t)u * UNIT : nullptr);
            if (u & 1) pend_v = u < 2 * n ? kb + (size_t)u * UNIT : nullptr;
            if (u && !(u & 3) && u < 2 * n) dep_wait(dep_cnt, ++ndep);
            if (src) {
              ACQ(UNIT);
              if (el) bulk_load_mc(dst + rank * 16384, src, 16384, fb);
            }
          }
        } else {
          const bool g1 = type == T_G1;
          const int h0 = (t.x >> 18) & 127, h1 = t.x >> 25, ga = h0 >> 1, n1 = ((h1 + 1) >> 1) - ga;
          const int la = (t.y >> 2) & 63, n2 = (int)((t.y >> 8) & 63) - la, qd = t.y & 3;
          const CUtensorMap* mb = &P.wq;
          int nb = idx * 4 + rank * 2;
          if (kind == K_KV) { mb = rank ? &P.wuv : &P.wuk; nb = idx * 2; }
          else if (kind == K_FFN) { mb = rank ? &P.wu : &P.wg; nb = idx * 2; }
#pragma unroll 1
          for (int gi = 0; gi < n1 + n2; gi++) {
            const int g = g1 ? (gi + (ti ? m : 0)) & 3 : c_gorder[(m * 2 + idx) * 46 + (gi < n1 ? ga + gi : la + gi - n1)];
            if (!g1 || (gi == 0 && kind == K_FFN)) dep_wait(dep_cnt, ++ndep);
            if (ti == 0 && gi < 3) {
              r.next();
            } else {
              ACQ(UNIT);
              if (el) {
                if (g1) tma4(dst, kind == K_KV ? &P.c : &P.x, 0, 64 * rank, 2 * g, 2 * m, fb);
                else bulk_load(dst, g_aimg + ((size_t)((m * 46 + g) * 2 + rank)) * UNIT, UNIT, fb);
              }
            }
            const bool late = gi >= n1;
#pragma unroll 1
            for (int hf = 0; hf < (late ? 1 : 2); hf++) {
              if (!late && (2 * (ga + gi) + hf < h0 || 2 * (ga + gi) + hf >= h1)) continue;
              if (ti == 0 && gi < 2) { r.next(); continue; }
              if (ti == 0 && gi == 2 && hf == 0) asm volatile("barrier.cluster.wait.aligned;" ::: "memory");
              ACQ(late ? UNIT / 2 : UNIT);
              if (el) {
                if (g1) {
                  tma3_mc(dst + rank * 16384, mb, 0, g * 128 + hf * 64, nb, fb);
                } else {
#pragma unroll 1
                  for (int e = 0; e < (late ? 1 : 2); e++) {
                    const uint32_t d = dst + (late ? rank * 8192 : rank * 16384 + e * 8192);
                    const int blk = idx * 4 + ((late ? 0 : rank * 2 + e) ^ qd), kh = late ? rank : hf;
                    if (g < 32) tma3_mc(d, &P.wo, 0, g * 128 + kh * 64, blk, fb);
                    else tma5_mc(d, &P.wd, blk * 64, (g - 32) * 4 + kh * 2, fb);
                  }
                }
              }
            }
          }
        }
      }
      if (el) mbar_arrive(bar_done);
    }
    __syncwarp();
    asm volatile("barrier.cluster.arrive.relaxed.aligned;\nbarrier.cluster.wait.aligned;" ::: "memory");
    if (threadIdx.x == 256) asm volatile("red.relaxed.gpu.global.add.u32 [%0], 1;" ::"l"(&g_epoch) : "memory");
  }
}

typedef CUresult (*EncodeFn)(CUtensorMap*, CUtensorMapDataType, cuuint32_t, void*, const cuuint64_t*, const cuuint64_t*, const cuuint32_t*, const cuuint32_t*,
                             CUtensorMapInterleave, CUtensorMapSwizzle, CUtensorMapL2promotion, CUtensorMapFloatOOBfill);

void encode(EncodeFn fn, CUtensorMap* m, const void* p, int rank, const cuuint64_t* dims, const cuuint64_t* strides, const cuuint32_t* box) {
  cuuint32_t es[5] = {1, 1, 1, 1, 1};
  fn(m, CU_TENSOR_MAP_DATA_TYPE_BFLOAT16, rank, const_cast<void*>(p), dims, strides, box, es, CU_TENSOR_MAP_INTERLEAVE_NONE, CU_TENSOR_MAP_SWIZZLE_128B,
     CU_TENSOR_MAP_L2_PROMOTION_L2_256B, CU_TENSOR_MAP_FLOAT_OOB_FILL_NONE);
}
void encode_act(EncodeFn fn, CUtensorMap* m, const void* p) {
  cuuint64_t d[4] = {64, 128, 8, 16}, s[3] = {1024, 128, 128 * 1024};
  cuuint32_t b[4] = {64, 64, 2, 2};
  encode(fn, m, p, 4, d, s, b);
}
void encode_w(EncodeFn fn, CUtensorMap* m, const void* p, int K, int N, int nblk = 2) {
  cuuint64_t d[3] = {64, (cuuint64_t)K, (cuuint64_t)N / 64}, s[2] = {(cuuint64_t)N * 2, 128};
  cuuint32_t b[3] = {64, 64, (cuuint32_t)nblk};
  encode(fn, m, p, 3, d, s, b);
}
void encode_wd(EncodeFn fn, CUtensorMap* m, const void* p) {
  cuuint64_t d[5] = {512, 2, 4, 4, 56}, s[4] = {1024, 8 * 1024, 2 * 1024, 32 * 1024};
  cuuint32_t b[5] = {64, 2, 4, 4, 2};
  encode(fn, m, p, 5, d, s, b);
}

}

extern "C" void kernel_launch(void* const* d_in, const int* in_sizes, int n_in, void* d_out, int out_size) {
  static EncodeFn fn = nullptr;
  if (!fn) {
    cudaDriverEntryPointQueryResult st;
    void* p = nullptr;
    cudaGetDriverEntryPoint("cuTensorMapEncodeTiled", &p, cudaEnableDefault, &st);
    fn = (EncodeFn)p;
    cudaFuncSetAttribute(mega_kernel, cudaFuncAttributeMaxDynamicSharedMemorySize, SMEM_BYTES);
  }
  Params P;
  encode_act(fn, &P.x, d_in[0]);
  encode_act(fn, &P.c, d_in[1]);
  encode_w(fn, &P.wq, d_in[2], 512, 4096);
  encode_w(fn, &P.wuk, d_in[3], 512, 4096);
  encode_w(fn, &P.wuv, d_in[4], 512, 4096);
  encode_w(fn, &P.wo, d_in[5], 4096, 512, 1);
  encode_w(fn, &P.wg, d_in[7], 512, 1792);
  encode_w(fn, &P.wu, d_in[8], 512, 1792);
  encode_wd(fn, &P.wd, d_in[9]);
  P.xp = (const __nv_bfloat16*)d_in[0];
  P.gw = (const __nv_bfloat16*)d_in[10];
  P.out = (__nv_bfloat16*)d_out;
  for (int i = 0; i < NCLUSTER; i++) P.first[i] = h_first[i];
  mega_kernel<<<NCTA, 384, SMEM_BYTES>>>(P);
}
```
